```python
import torch

def _softmax(x, axis=-1):
    return torch.softmax(x, dim=axis)

def _gelu(x):
    return torch.nn.functional.gelu(x, approximate='tanh')

def _silu(x):
    return torch.nn.functional.silu(x)

def _sigmoid(x):
    return torch.sigmoid(x)

def _layernorm(x, axis=-1, eps=1e-05):
    m = x.mean(dim=axis, keepdim=True)
    v = x.var(dim=axis, keepdim=True, unbiased=False)
    return (x - m) / torch.sqrt(v + eps)

def _scatter_add(tgt, idx, src, axis=0):
    return tgt.clone().index_add_(axis, idx, src)

def _segment_sum(src, seg, n):
    out = torch.zeros((n,) + src.shape[1:], dtype=src.dtype)
    return out.index_add_(0, seg, src)

def _pad(x, pw):
    flat = tuple((v for pair in reversed(pw) for v in pair))
    return torch.nn.functional.pad(x, flat)
kernel_name = 'sequential_preLN__memory_aug_recurrent_mem_tr__dense_activation_gelu__prompt'

def setup_inputs():

    _w = lambda a: (lambda t: t.to(torch.bfloat16) if t.is_floating_point() else t)(torch.as_tensor(a))

    def _A_setup():
        B, S, Dm = (1, 2048, 576)
        H, Dh = (32, 128)
        M, seg = (8, 32)
        seg = min(seg, S)
        S = S // seg * seg
        return {'x': _w((lambda *s: torch.randn(*s, dtype=torch.bfloat16) * 0.05)(B, S, Dm)), 'mem0': _w((lambda *s: torch.randn(*s, dtype=torch.bfloat16) * 0.2)(B, M, Dm)), 'Wq': _w((lambda *s: torch.randn(*s, dtype=torch.bfloat16) * 1.6)(Dm, H, Dh) * Dm ** (-0.5)), 'Wk': _w((lambda *s: torch.randn(*s, dtype=torch.bfloat16) * 1.6)(Dm, H, Dh) * Dm ** (-0.5)), 'Wv': _w((lambda *s: torch.randn(*s, dtype=torch.bfloat16) * 0.2)(Dm, H, Dh) * Dm ** (-0.5)), 'Wo': _w((lambda *s: torch.randn(*s, dtype=torch.bfloat16) * 0.2)(H, Dh, Dm) * (H * Dh) ** (-0.5)), 'seg_len': seg}
    _A_in = _A_setup()

    def _B_setup():
        B, S, D, F = (1, 2048, 576, 4608)
        return {'x': _w((lambda *s: torch.randn(*s, dtype=torch.bfloat16) * 0.05)(B, S, D)), 'w1': _w((lambda *s: torch.randn(*s, dtype=torch.bfloat16) * 0.4)(D, F) * D ** (-0.5)), 'b1': _w((lambda *s: torch.randn(*s, dtype=torch.bfloat16) * 12.8)(F) * 0.01), 'w2': _w((lambda *s: torch.randn(*s, dtype=torch.bfloat16) * 0.2)(F, D) * F ** (-0.5)), 'b2': _w((lambda *s: torch.randn(*s, dtype=torch.bfloat16) * 3.2)(D) * 0.01)}
    _B_in = _B_setup()
    return {'A_x': _A_in['x'], 'A_mem0': _A_in['mem0'], 'A_Wq': _A_in['Wq'], 'A_Wk': _A_in['Wk'], 'A_Wv': _A_in['Wv'], 'A_Wo': _A_in['Wo'], 'A_seg_len': _A_in['seg_len'], 'B_x': _B_in['x'], 'B_w1': _B_in['w1'], 'B_b1': _B_in['b1'], 'B_w2': _B_in['w2'], 'B_b2': _B_in['b2']}

def reference(A_x, A_mem0, A_Wq, A_Wk, A_Wv, A_Wo, A_seg_len, B_x, B_w1, B_b1, B_w2, B_b2):

    def _A_ref(x, mem0, Wq, Wk, Wv, Wo, seg_len):
        B, S, Dm = x.shape
        H, Dh = (Wq.shape[1], Wq.shape[2])
        M = mem0.shape[1]
        scale = Dh ** (-0.5)
        n_seg = S // seg_len
        L = M + seg_len
        idx = torch.arange(L)
        mask = (idx[:, None] < M) | (idx[:, None] >= idx[None, :])
        mem = mem0
        outs = []
        for s in range(n_seg):
            xs = x[:, s * seg_len:(s + 1) * seg_len, :].clone()
            h = torch.concatenate([mem, xs], axis=1)
            q = torch.einsum('btd,dhe->bhte', h, Wq)
            k = torch.einsum('btd,dhe->bhte', h, Wk)
            v = torch.einsum('btd,dhe->bhte', h, Wv)
            scores = torch.einsum('bhqe,bhke->bhqk', q, k) * scale
            scores = torch.where(mask[None, None], scores, -1000000000.0)
            p = _softmax(scores, axis=-1)
            o = torch.einsum('bhqk,bhke->bhqe', p, v)
            o = torch.einsum('bhte,hed->btd', o, Wo)
            mem = o[:, :M, :].clone()
            outs.append(o[:, M:, :])
        return torch.concatenate(outs, axis=1)

    def _B_ref(x, w1, b1, w2, b2):
        h = torch.einsum('bsd,df->bsf', x, w1) + b1
        h = _gelu(h)
        return torch.einsum('bsf,fd->bsd', h, w2) + b2
    x = A_x
    h = x + _A_ref(_layernorm(x, axis=-1), A_mem0, A_Wq, A_Wk, A_Wv, A_Wo, A_seg_len)
    h2 = h + _B_ref(_layernorm(h, axis=-1), B_w1, B_b1, B_w2, B_b2)
    return h2
```

```cpp
#include <cuda_runtime.h>
#include <cuda_bf16.h>
#include <cuda.h>
#include <stdint.h>

typedef __nv_bfloat16 bf16;

constexpr int SEQ = 2048, DM = 576, NH = 32, DH = 128, HD = 4096, FF = 4608, NSEG = 64, NRB = 16;

__device__ __align__(1024) uint4 g_Kf[NH * 256 * 4 * 32];
__device__ __align__(1024) uint4 g_Vf[NH * NSEG * 128 * 4];
__device__ __align__(1024) uint4 g_Kmf[NH * NSEG * 4 * 32];
__device__ __align__(1024) uint4 g_Vmf[NH * NSEG * 4 * 32];
__device__ __align__(8192) uint4 g_xch[64 * 512];
__device__ unsigned g_kvflag[NRB * 64];
__device__ unsigned g_memflag[NH * 8];
__device__ unsigned g_epoch;
__device__ unsigned g_resident;
__device__ unsigned g_err;

__device__ __forceinline__ uint32_t smem_u32(const void* p) { return (uint32_t)__cvta_generic_to_shared(p); }
__device__ __forceinline__ void mbar_init(uint32_t a, int cnt) { asm volatile("mbarrier.init.shared::cta.b64 [%0], %1;" :: "r"(a), "r"(cnt) : "memory"); }
__device__ __forceinline__ void mbar_expect(uint32_t a, int bytes) { asm volatile("mbarrier.arrive.expect_tx.shared::cta.b64 _, [%0], %1;" :: "r"(a), "r"(bytes) : "memory"); }
__device__ __forceinline__ void mbar_arrive(uint32_t a) { asm volatile("mbarrier.arrive.shared::cta.b64 _, [%0];" :: "r"(a) : "memory"); }
__device__ __forceinline__ bool mbar_try(uint32_t a, uint32_t parity) {
  uint32_t ok;
  asm volatile("{ .reg .pred p; mbarrier.try_wait.parity.shared::cta.b64 p, [%1], %2; selp.u32 %0, 1, 0, p; }" : "=r"(ok) : "r"(a), "r"(parity) : "memory");
  return ok;
}
__device__ __forceinline__ bool mbar_try_cl(uint32_t a, uint32_t parity) {
  uint32_t ok;
  asm volatile("{ .reg .pred p; mbarrier.try_wait.parity.acquire.cluster.shared::cta.b64 p, [%1], %2; selp.u32 %0, 1, 0, p; }" : "=r"(ok) : "r"(a), "r"(parity) : "memory");
  return ok;
}
__device__ __forceinline__ uint32_t clk32() { uint32_t c; asm volatile("mov.u32 %0, %%clock;" : "=r"(c)); return c; }
constexpr uint32_t TIMEOUT_CLKS = 400000000u;
__device__ __forceinline__ bool timed_out(uint32_t t0) {
  if (clk32() - t0 > TIMEOUT_CLKS) { g_err = 1; return true; }
  return false;
}
__device__ __forceinline__ void mbar_wait(uint32_t a, uint32_t parity, uint32_t t0) {
  while (!mbar_try(a, parity)) { if (timed_out(t0)) break; }
}
__device__ __forceinline__ void mbar_wait_cl(uint32_t a, uint32_t parity, uint32_t t0) {
  while (!mbar_try_cl(a, parity)) { if (timed_out(t0)) break; }
}
__device__ __forceinline__ uint32_t mapa(uint32_t a, uint32_t r) { uint32_t d; asm volatile("mapa.shared::cluster.u32 %0, %1, %2;" : "=r"(d) : "r"(a), "r"(r)); return d; }
__device__ __forceinline__ void st_async16(uint32_t a, uint32_t x, uint32_t y, uint32_t z, uint32_t w, uint32_t bar) {
  asm volatile("st.async.shared::cluster.mbarrier::complete_tx::bytes.v4.b32 [%0], {%1,%2,%3,%4}, [%5];" :: "r"(a), "r"(x), "r"(y), "r"(z), "r"(w), "r"(bar) : "memory");
}
__device__ __forceinline__ void st_async8(uint32_t a, uint32_t x, uint32_t y, uint32_t bar) {
  asm volatile("st.async.shared::cluster.mbarrier::complete_tx::bytes.v2.b32 [%0], {%1,%2}, [%3];" :: "r"(a), "r"(x), "r"(y), "r"(bar) : "memory");
}
__device__ __forceinline__ void bar_sync(int id, int n) { asm volatile("bar.sync %0, %1;" :: "r"(id), "r"(n) : "memory"); }
__device__ __forceinline__ void bar_arrive(int id, int n) { asm volatile("bar.arrive %0, %1;" :: "r"(id), "r"(n) : "memory"); }
__device__ __forceinline__ void cluster_sync() { asm volatile("barrier.cluster.arrive.release.aligned; barrier.cluster.wait.acquire.aligned;" ::: "memory"); }
__device__ __forceinline__ uint32_t pack2(float lo, float hi) { uint32_t d; asm("cvt.rn.bf16x2.f32 %0, %1, %2;" : "=r"(d) : "f"(hi), "f"(lo)); return d; }
__device__ __forceinline__ float bflo(uint32_t v) { return __uint_as_float(v << 16); }
__device__ __forceinline__ float bfhi(uint32_t v) { return __uint_as_float(v & 0xffff0000u); }
__device__ __forceinline__ uint32_t movmat(uint32_t a) { uint32_t d; asm volatile("movmatrix.sync.aligned.m8n8.trans.b16 %0, %1;" : "=r"(d) : "r"(a)); return d; }
__device__ __forceinline__ uint32_t hadd2bf(uint32_t a, uint32_t b) { uint32_t d; asm("add.rn.bf16x2 %0, %1, %2;" : "=r"(d) : "r"(a), "r"(b)); return d; }
__device__ __forceinline__ void mma16816(float (&c)[4], uint32_t a0, uint32_t a1, uint32_t a2, uint32_t a3, uint32_t b0, uint32_t b1) {
  asm volatile("mma.sync.aligned.m16n8k16.row.col.f32.bf16.bf16.f32 {%0,%1,%2,%3}, {%4,%5,%6,%7}, {%8,%9}, {%0,%1,%2,%3};"
    : "+f"(c[0]), "+f"(c[1]), "+f"(c[2]), "+f"(c[3]) : "r"(a0), "r"(a1), "r"(a2), "r"(a3), "r"(b0), "r"(b1));
}
__device__ __forceinline__ void mma16816(float (&c)[4], const uint32_t (&a)[4], uint32_t b0, uint32_t b1) { mma16816(c, a[0], a[1], a[2], a[3], b0, b1); }
__device__ __forceinline__ void mma1688(float (&c)[4], uint32_t a0, uint32_t a1, uint32_t b0) {
  asm volatile("mma.sync.aligned.m16n8k8.row.col.f32.bf16.bf16.f32 {%0,%1,%2,%3}, {%4,%5}, {%6}, {%0,%1,%2,%3};"
    : "+f"(c[0]), "+f"(c[1]), "+f"(c[2]), "+f"(c[3]) : "r"(a0), "r"(a1), "r"(b0));
}
__device__ __forceinline__ void ldsm4t(uint32_t (&r)[4], uint32_t a) {
  asm volatile("ldmatrix.sync.aligned.m8n8.x4.trans.shared.b16 {%0,%1,%2,%3}, [%4];" : "=r"(r[0]), "=r"(r[1]), "=r"(r[2]), "=r"(r[3]) : "r"(a) : "memory");
}
__device__ __forceinline__ uint4 lds128(uint32_t a) { uint4 v; asm volatile("ld.shared.v4.b32 {%0,%1,%2,%3}, [%4];" : "=r"(v.x), "=r"(v.y), "=r"(v.z), "=r"(v.w) : "r"(a) : "memory"); return v; }
__device__ __forceinline__ uint2 lds64(uint32_t a) { uint2 v; asm volatile("ld.shared.v2.b32 {%0,%1}, [%2];" : "=r"(v.x), "=r"(v.y) : "r"(a) : "memory"); return v; }
__device__ __forceinline__ void sts128(uint32_t a, uint32_t x, uint32_t y, uint32_t z, uint32_t w) { asm volatile("st.shared.v4.b32 [%0], {%1,%2,%3,%4};" :: "r"(a), "r"(x), "r"(y), "r"(z), "r"(w) : "memory"); }
__device__ __forceinline__ void sts64(uint32_t a, uint32_t x, uint32_t y) { asm volatile("st.shared.v2.b32 [%0], {%1,%2};" :: "r"(a), "r"(x), "r"(y) : "memory"); }
__device__ __forceinline__ void sts32(uint32_t a, uint32_t x) { asm volatile("st.shared.b32 [%0], %1;" :: "r"(a), "r"(x) : "memory"); }
__device__ __forceinline__ void cp_async16(uint32_t dst, const void* src) { asm volatile("cp.async.cg.shared.global [%0], [%1], 16;" :: "r"(dst), "l"(src) : "memory"); }
__device__ __forceinline__ void cp_async_wait_all() { asm volatile("cp.async.wait_all;" ::: "memory"); }
__device__ __forceinline__ uint4 ldg_cg(const void* p) { uint4 v; asm volatile("ld.global.cg.v4.b32 {%0,%1,%2,%3}, [%4];" : "=r"(v.x), "=r"(v.y), "=r"(v.z), "=r"(v.w) : "l"(p) : "memory"); return v; }
__device__ __forceinline__ uint4 ld_relaxed16(const void* p) { uint4 v; asm volatile("ld.relaxed.gpu.global.v4.b32 {%0,%1,%2,%3}, [%4];" : "=r"(v.x), "=r"(v.y), "=r"(v.z), "=r"(v.w) : "l"(p) : "memory"); return v; }
__device__ __forceinline__ void st_relaxed16(void* p, uint32_t x, uint32_t y, uint32_t z, uint32_t w) { asm volatile("st.relaxed.gpu.global.v4.b32 [%0], {%1,%2,%3,%4};" :: "l"(p), "r"(x), "r"(y), "r"(z), "r"(w) : "memory"); }
__device__ __forceinline__ unsigned ld_acquire(const unsigned* p) { unsigned v; asm volatile("ld.acquire.gpu.global.u32 %0, [%1];" : "=r"(v) : "l"(p) : "memory"); return v; }
__device__ __forceinline__ void st_release(unsigned* p, unsigned v) { asm volatile("st.release.gpu.global.u32 [%0], %1;" :: "l"(p), "r"(v) : "memory"); }
__device__ __forceinline__ float ex2(float x) { float y; asm("ex2.approx.ftz.f32 %0, %1;" : "=f"(y) : "f"(x)); return y; }

__device__ __forceinline__ void st_b128(void* p, uint32_t x, uint32_t y, uint32_t z, uint32_t w) {
  asm volatile("{ .reg .b128 t; .reg .b64 lo, hi; mov.b64 lo, {%1,%2}; mov.b64 hi, {%3,%4}; mov.b128 t, {lo,hi}; st.relaxed.gpu.global.b128 [%0], t; }"
    :: "l"(p), "r"(x), "r"(y), "r"(z), "r"(w) : "memory");
}
__device__ __forceinline__ uint4 ld_b128(const void* p) {
  uint4 v;
  asm volatile("{ .reg .b128 t; .reg .b64 lo, hi; ld.relaxed.gpu.global.b128 t, [%4]; mov.b128 {lo,hi}, t; mov.b64 {%0,%1}, lo; mov.b64 {%2,%3}, hi; }"
    : "=r"(v.x), "=r"(v.y), "=r"(v.z), "=r"(v.w) : "l"(p) : "memory");
  return v;
}
__device__ __forceinline__ void wg_fence() { asm volatile("wgmma.fence.sync.aligned;" ::: "memory"); }
__device__ __forceinline__ void wg_commit() { asm volatile("wgmma.commit_group.sync.aligned;" ::: "memory"); }
template <int N> __device__ __forceinline__ void wg_wait() { asm volatile("wgmma.wait_group.sync.aligned %0;" :: "n"(N) : "memory"); }
__device__ __forceinline__ uint64_t make_desc(uint32_t addr, uint32_t lbo, uint32_t sbo, uint32_t mode) {
  return (uint64_t)((addr & 0x3FFFF) >> 4) | ((uint64_t)(lbo >> 4) << 16) | ((uint64_t)(sbo >> 4) << 32) | ((uint64_t)mode << 62);
}
__device__ __forceinline__ void tma2d(uint32_t dst, const CUtensorMap* m, int c0, int c1, uint32_t bar) {
  asm volatile("cp.async.bulk.tensor.2d.shared::cluster.global.mbarrier::complete_tx::bytes [%0], [%1, {%3, %4}], [%2];"
    :: "r"(dst), "l"(m), "r"(bar), "r"(c0), "r"(c1) : "memory");
}
__device__ __forceinline__ void tma5d(uint32_t dst, const CUtensorMap* m, int c0, int c4, uint32_t bar) {
  asm volatile("cp.async.bulk.tensor.5d.shared::cluster.global.mbarrier::complete_tx::bytes [%0], [%1, {%3, %5, %5, %5, %4}], [%2];"
    :: "r"(dst), "l"(m), "r"(bar), "r"(c0), "r"(c4), "r"(0) : "memory");
}
__device__ __forceinline__ void bulk_g2s(uint32_t dst, const void* src, uint32_t bytes, uint32_t bar) {
  asm volatile("cp.async.bulk.shared::cluster.global.mbarrier::complete_tx::bytes [%0], [%1], %2, [%3];" :: "r"(dst), "l"(src), "r"(bytes), "r"(bar) : "memory");
}
__device__ __forceinline__ void stg128(void* p, uint32_t x, uint32_t y, uint32_t z, uint32_t w) {
  asm volatile("st.global.v4.b32 [%0], {%1,%2,%3,%4};" :: "l"(p), "r"(x), "r"(y), "r"(z), "r"(w) : "memory");
}
template <int N> __device__ __forceinline__ void fence_regs(float (&d)[N]) {
#pragma unroll
  for (int i = 0; i < N; i++) asm volatile("" : "+f"(d[i]) :: "memory");
}
template <int TA, int TB>
__device__ __forceinline__ void wgmma_n128(float (&d)[64], uint64_t da, uint64_t db, int scale_d) {
  asm volatile("{ .reg .pred p; setp.ne.b32 p, %66, 0;\n"
    "wgmma.mma_async.sync.aligned.m64n128k16.f32.bf16.bf16 {%0, %1, %2, %3, %4, %5, %6, %7, %8, %9, %10, %11, %12, %13, %14, %15, %16, %17, %18, %19, %20, %21, %22, %23, %24, %25, %26, %27, %28, %29, %30, %31, %32, %33, %34, %35, %36, %37, %38, %39, %40, %41, %42, %43, %44, %45, %46, %47, %48, %49, %50, %51, %52, %53, %54, %55, %56, %57, %58, %59, %60, %61, %62, %63}, %64, %65, p, 1, 1, %67, %68; }"
    : "+f"(d[0]), "+f"(d[1]), "+f"(d[2]), "+f"(d[3]), "+f"(d[4]), "+f"(d[5]), "+f"(d[6]), "+f"(d[7]), "+f"(d[8]), "+f"(d[9]), "+f"(d[10]), "+f"(d[11]), "+f"(d[12]), "+f"(d[13]), "+f"(d[14]), "+f"(d[15]), "+f"(d[16]), "+f"(d[17]), "+f"(d[18]), "+f"(d[19]), "+f"(d[20]), "+f"(d[21]), "+f"(d[22]), "+f"(d[23]), "+f"(d[24]), "+f"(d[25]), "+f"(d[26]), "+f"(d[27]), "+f"(d[28]), "+f"(d[29]), "+f"(d[30]), "+f"(d[31]), "+f"(d[32]), "+f"(d[33]), "+f"(d[34]), "+f"(d[35]), "+f"(d[36]), "+f"(d[37]), "+f"(d[38]), "+f"(d[39]), "+f"(d[40]), "+f"(d[41]), "+f"(d[42]), "+f"(d[43]), "+f"(d[44]), "+f"(d[45]), "+f"(d[46]), "+f"(d[47]), "+f"(d[48]), "+f"(d[49]), "+f"(d[50]), "+f"(d[51]), "+f"(d[52]), "+f"(d[53]), "+f"(d[54]), "+f"(d[55]), "+f"(d[56]), "+f"(d[57]), "+f"(d[58]), "+f"(d[59]), "+f"(d[60]), "+f"(d[61]), "+f"(d[62]), "+f"(d[63])
    : "l"(da), "l"(db), "r"(scale_d), "n"(TA), "n"(TB));
}
template <int TA, int TB>
__device__ __forceinline__ void wgmma_n160(float (&d)[80], uint64_t da, uint64_t db, int scale_d) {
  asm volatile("{ .reg .pred p; setp.ne.b32 p, %82, 0;\n"
    "wgmma.mma_async.sync.aligned.m64n160k16.f32.bf16.bf16 {%0, %1, %2, %3, %4, %5, %6, %7, %8, %9, %10, %11, %12, %13, %14, %15, %16, %17, %18, %19, %20, %21, %22, %23, %24, %25, %26, %27, %28, %29, %30, %31, %32, %33, %34, %35, %36, %37, %38, %39, %40, %41, %42, %43, %44, %45, %46, %47, %48, %49, %50, %51, %52, %53, %54, %55, %56, %57, %58, %59, %60, %61, %62, %63, %64, %65, %66, %67, %68, %69, %70, %71, %72, %73, %74, %75, %76, %77, %78, %79}, %80, %81, p, 1, 1, %83, %84; }"
    : "+f"(d[0]), "+f"(d[1]), "+f"(d[2]), "+f"(d[3]), "+f"(d[4]), "+f"(d[5]), "+f"(d[6]), "+f"(d[7]), "+f"(d[8]), "+f"(d[9]), "+f"(d[10]), "+f"(d[11]), "+f"(d[12]), "+f"(d[13]), "+f"(d[14]), "+f"(d[15]), "+f"(d[16]), "+f"(d[17]), "+f"(d[18]), "+f"(d[19]), "+f"(d[20]), "+f"(d[21]), "+f"(d[22]), "+f"(d[23]), "+f"(d[24]), "+f"(d[25]), "+f"(d[26]), "+f"(d[27]), "+f"(d[28]), "+f"(d[29]), "+f"(d[30]), "+f"(d[31]), "+f"(d[32]), "+f"(d[33]), "+f"(d[34]), "+f"(d[35]), "+f"(d[36]), "+f"(d[37]), "+f"(d[38]), "+f"(d[39]), "+f"(d[40]), "+f"(d[41]), "+f"(d[42]), "+f"(d[43]), "+f"(d[44]), "+f"(d[45]), "+f"(d[46]), "+f"(d[47]), "+f"(d[48]), "+f"(d[49]), "+f"(d[50]), "+f"(d[51]), "+f"(d[52]), "+f"(d[53]), "+f"(d[54]), "+f"(d[55]), "+f"(d[56]), "+f"(d[57]), "+f"(d[58]), "+f"(d[59]), "+f"(d[60]), "+f"(d[61]), "+f"(d[62]), "+f"(d[63]), "+f"(d[64]), "+f"(d[65]), "+f"(d[66]), "+f"(d[67]), "+f"(d[68]), "+f"(d[69]), "+f"(d[70]), "+f"(d[71]), "+f"(d[72]), "+f"(d[73]), "+f"(d[74]), "+f"(d[75]), "+f"(d[76]), "+f"(d[77]), "+f"(d[78]), "+f"(d[79])
    : "l"(da), "l"(db), "r"(scale_d), "n"(TA), "n"(TB));
}
template <int TA, int TB>
__device__ __forceinline__ void wgmma_n192(float (&d)[96], uint64_t da, uint64_t db, int scale_d) {
  asm volatile("{ .reg .pred p; setp.ne.b32 p, %98, 0;\n"
    "wgmma.mma_async.sync.aligned.m64n192k16.f32.bf16.bf16 {%0, %1, %2, %3, %4, %5, %6, %7, %8, %9, %10, %11, %12, %13, %14, %15, %16, %17, %18, %19, %20, %21, %22, %23, %24, %25, %26, %27, %28, %29, %30, %31, %32, %33, %34, %35, %36, %37, %38, %39, %40, %41, %42, %43, %44, %45, %46, %47, %48, %49, %50, %51, %52, %53, %54, %55, %56, %57, %58, %59, %60, %61, %62, %63, %64, %65, %66, %67, %68, %69, %70, %71, %72, %73, %74, %75, %76, %77, %78, %79, %80, %81, %82, %83, %84, %85, %86, %87, %88, %89, %90, %91, %92, %93, %94, %95}, %96, %97, p, 1, 1, %99, %100; }"
    : "+f"(d[0]), "+f"(d[1]), "+f"(d[2]), "+f"(d[3]), "+f"(d[4]), "+f"(d[5]), "+f"(d[6]), "+f"(d[7]), "+f"(d[8]), "+f"(d[9]), "+f"(d[10]), "+f"(d[11]), "+f"(d[12]), "+f"(d[13]), "+f"(d[14]), "+f"(d[15]), "+f"(d[16]), "+f"(d[17]), "+f"(d[18]), "+f"(d[19]), "+f"(d[20]), "+f"(d[21]), "+f"(d[22]), "+f"(d[23]), "+f"(d[24]), "+f"(d[25]), "+f"(d[26]), "+f"(d[27]), "+f"(d[28]), "+f"(d[29]), "+f"(d[30]), "+f"(d[31]), "+f"(d[32]), "+f"(d[33]), "+f"(d[34]), "+f"(d[35]), "+f"(d[36]), "+f"(d[37]), "+f"(d[38]), "+f"(d[39]), "+f"(d[40]), "+f"(d[41]), "+f"(d[42]), "+f"(d[43]), "+f"(d[44]), "+f"(d[45]), "+f"(d[46]), "+f"(d[47]), "+f"(d[48]), "+f"(d[49]), "+f"(d[50]), "+f"(d[51]), "+f"(d[52]), "+f"(d[53]), "+f"(d[54]), "+f"(d[55]), "+f"(d[56]), "+f"(d[57]), "+f"(d[58]), "+f"(d[59]), "+f"(d[60]), "+f"(d[61]), "+f"(d[62]), "+f"(d[63]), "+f"(d[64]), "+f"(d[65]), "+f"(d[66]), "+f"(d[67]), "+f"(d[68]), "+f"(d[69]), "+f"(d[70]), "+f"(d[71]), "+f"(d[72]), "+f"(d[73]), "+f"(d[74]), "+f"(d[75]), "+f"(d[76]), "+f"(d[77]), "+f"(d[78]), "+f"(d[79]), "+f"(d[80]), "+f"(d[81]), "+f"(d[82]), "+f"(d[83]), "+f"(d[84]), "+f"(d[85]), "+f"(d[86]), "+f"(d[87]), "+f"(d[88]), "+f"(d[89]), "+f"(d[90]), "+f"(d[91]), "+f"(d[92]), "+f"(d[93]), "+f"(d[94]), "+f"(d[95])
    : "l"(da), "l"(db), "r"(scale_d), "n"(TA), "n"(TB));
}
namespace chain {
constexpr int UNIT = 512;
constexpr int NX = 8;
constexpr int NPV = 9;
constexpr int NV2 = 18 - NPV;
constexpr int U_V2 = 2 * NX, U_WO = U_V2 + NV2, WREG_UNITS = U_WO + 16;
constexpr int NPERM = 2 * (18 - NX) + NPV;
constexpr int STG_UNITS = 47 - WREG_UNITS;
constexpr int SM_W = 0;
constexpr int SM_WOX = SM_W + 8 * WREG_UNITS * UNIT;
constexpr int SM_STG = SM_WOX + 16 * UNIT;
constexpr int SM_KX = SM_STG, SM_VX = SM_STG + 8192, SM_OV = SM_STG + 16384;
static_assert(8 * STG_UNITS * UNIT >= 16384 + 2048, "");
constexpr int SM_MEM = SM_STG + 8 * STG_UNITS * UNIT;
constexpr int SM_OQK = SM_MEM + 9 * 512;
constexpr int SM_XQK = SM_OQK + 4096;
constexpr int SM_XV = SM_XQK + 4096;
constexpr int SM_S = SM_XV + 2048;
constexpr int SM_O = SM_S + 1536;
constexpr int SM_RS = SM_O + 2048;
constexpr int SM_BAR = SM_RS + 8 * 576;
constexpr int SM_PROF = SM_BAR + 128;
constexpr int SM_TOTAL = SM_PROF + 256;
constexpr int B_AG0 = 0, B_AG1 = 8, B_AG2 = 16, B_AG3 = 24, B_XQK = 32, B_XV = 40, B_RS = 48, B_KV = 56;
constexpr int AG1_BYTES = 2 * 576, AG2_BYTES = 3 * 576, AG3_BYTES = 2 * 576;
constexpr int RS_BYTES = 7 * 512 + 8 * 64;
constexpr int BAR_OQK = 1, BAR_S = 2, BAR_O = 3, BAR_ALL = 4;
constexpr int NTHREADS = 384;
constexpr int REG_C = 216, REG_A = 72;
static_assert(2 * REG_C + REG_A <= 504, "register pool");

#define PROF(slot) do {} while (0)
#define PROFN(slot) do {} while (0)
#define PROFS() do {} while (0)

__device__ __forceinline__ void load_unit(uint32_t dst, const bf16* W, int ld, int k0, int m0, int lane) {
  int mat = lane >> 3, r = lane & 7;
  cp_async16(dst + lane * 16, W + (size_t)(k0 + (mat >> 1) * 8 + r) * ld + m0 + (mat & 1) * 8);
}
__device__ __forceinline__ void mmaq(float (&c)[4], const uint4& a, uint32_t b0, uint32_t b1) { mma16816(c, a.x, a.y, a.z, a.w, b0, b1); }

__device__ __forceinline__ int opaque(int v) { int d; asm volatile("mov.u32 %0, %1;" : "=r"(d) : "r"(v)); return d; }
constexpr int PACE = 1;
__device__ __forceinline__ uint32_t dep(uint32_t base, uint32_t v, uint32_t zero) {
  uint32_t d; asm("lop3.b32 %0, %1, %2, %3, 0xF8;" : "=r"(d) : "r"(base), "r"(v), "r"(zero)); return d;
}
__device__ __forceinline__ void softmax_pv(int s, int x, uint32_t sb, uint32_t sl, uint32_t bar, int lane_in, int a, int head, uint32_t t0, int P) {
  const int lane = opaque(lane_in);
  uint4* const vm_ptr = g_Vmf + (size_t)head * NSEG * 128 + x * 32 + lane;
  const float sc = 0.08838834764831845f * 1.4426950408889634f;
  const bool okv = mbar_try(bar + B_XV, s & 1);
  uint4 vx[4];
#pragma unroll
  for (int u = 0; u < 4; u++) vx[u] = lds128(sl + SM_VX + x * 2048 + u * 512);
  bar_sync(BAR_S, 128);
  const uint4 s0 = lds128(sl + SM_S), s1 = lds128(sl + SM_S + 512);
  const uint4 s2 = lds128(sl + SM_S + 1024);
  if (!okv) mbar_wait(bar + B_XV, s & 1, t0);
  const uint32_t lv = sb + x * 512 + lane * 8;
  const uint2 ov0 = lds64(lv + SM_OV), xv0 = lds64(lv + SM_XV), ov1 = lds64(lv + SM_OV + 256), xv1 = lds64(lv + SM_XV + 256);
  float y[10] = {__uint_as_float(s0.x), __uint_as_float(s0.y), __uint_as_float(s0.z), __uint_as_float(s0.w),
                 __uint_as_float(s1.x), __uint_as_float(s1.y), __uint_as_float(s1.z), __uint_as_float(s1.w),
                 __uint_as_float(s2.x) + __uint_as_float(s2.z), __uint_as_float(s2.y) + __uint_as_float(s2.w)};
  float m = fmaxf(fmaxf(fmaxf(y[0], y[1]), fmaxf(y[2], y[3])), fmaxf(fmaxf(y[4], y[5]), fmaxf(y[6], y[7])));
  m = fmaxf(m, fmaxf(y[8], y[9]));
  if (P) PROF(12);
  m = fmaxf(m, __shfl_xor_sync(0xffffffffu, m, 1));
  m = fmaxf(m, __shfl_xor_sync(0xffffffffu, m, 2));
  const float mc = m * sc;
#pragma unroll
  for (int i = 0; i < 10; i++) y[i] = ex2(fmaf(y[i], sc, -mc));
  const uint32_t p0 = pack2(y[0], y[1]), p1 = pack2(y[2], y[3]), p2 = pack2(y[4], y[5]), p3 = pack2(y[6], y[7]), p4 = pack2(y[8], y[9]);
  const uint4 vm = make_uint4(hadd2bf(ov0.x, xv0.x), hadd2bf(ov0.y, xv0.y), hadd2bf(ov1.x, xv1.x), hadd2bf(ov1.y, xv1.y));
  float o0[4] = {0.f, 0.f, 0.f, 0.f}, o1[4] = {0.f, 0.f, 0.f, 0.f}, o2[4] = {0.f, 0.f, 0.f, 0.f}, o3[4] = {0.f, 0.f, 0.f, 0.f};
  mmaq(o0, vx[0], p0, p1); mmaq(o2, vx[2], p0, p1);
  mmaq(o1, vx[1], p2, p3); mmaq(o3, vx[3], p2, p3);
  mma1688(o0, vm.x, vm.y, p4); mma1688(o2, vm.z, vm.w, p4);
  float l = ((y[0] + y[1]) + (y[2] + y[3])) + ((y[4] + y[5]) + (y[6] + y[7])) + (y[8] + y[9]);
  l += __shfl_xor_sync(0xffffffffu, l, 1);
  l += __shfl_xor_sync(0xffffffffu, l, 2);
  float inv; asm("rcp.approx.ftz.f32 %0, %1;" : "=f"(inv) : "f"(l));
  const float i0 = __shfl_sync(0xffffffffu, inv, (lane & 3) * 8), i1 = __shfl_sync(0xffffffffu, inv, (lane & 3) * 8 + 4);
  const uint32_t c0 = movmat(pack2((o0[0] + o1[0]) * i0, (o0[1] + o1[1]) * i1));
  const uint32_t c1 = movmat(pack2((o0[2] + o1[2]) * i0, (o0[3] + o1[3]) * i1));
  const uint32_t c2 = movmat(pack2((o2[0] + o3[0]) * i0, (o2[1] + o3[1]) * i1));
  const uint32_t c3 = movmat(pack2((o2[2] + o3[2]) * i0, (o2[3] + o3[3]) * i1));
  sts128(sl + SM_O + x * 512, c0, c1, c2, c3);
  if (a == 0) vm_ptr[(size_t)s * 128] = vm;
  if (P) PROF(13);
}

struct RedCtx { uint32_t rs_addr, mem_addr, mem_step, ranks; int hc; bool act; };

__device__ __forceinline__ void reduce_exchange(int x, int gi, int a, int s, uint32_t sb, uint32_t bar, int lane_in, uint32_t t0, int P) {
  const int lane = opaque(lane_in);
  RedCtx c;
  const int tt = x * 32 + lane;
  c.act = tt < 72;
  c.hc = lane & 1;
  c.rs_addr = sb + SM_RS + tt * 8;
  c.mem_addr = sb + SM_MEM + (x < 2 ? (tt >> 1) * 16 : 8 * 512 + (4 * gi + (lane >> 1)) * 16);
  c.mem_step = x < 2 ? 512 : 0;
  {
    const uint32_t r0 = (uint32_t)(2 * ((gi - 1) & 7) + a) | (uint32_t)(2 * ((gi - 3) & 7) + a) << 8 | (uint32_t)(2 * ((gi - 5) & 7) + a) << 16 | (uint32_t)(2 * ((gi - 7) & 7) + a) << 24;
    const uint32_t r1 = (uint32_t)(2 * ((gi - 2) & 7) + a) | (uint32_t)(2 * ((gi - 4) & 7) + a) << 8 | (uint32_t)(2 * ((gi - 6) & 7) + a) << 16;
    c.ranks = c.hc ? r1 : r0;
  }
  const uint32_t ma = c.mem_addr + (1 + c.hc) * c.mem_step;
  const uint32_t d0 = mapa(ma, c.ranks & 255), e0 = mapa(bar + B_AG1, c.ranks & 255);
  const uint32_t d1 = mapa(ma + 2 * c.mem_step, (c.ranks >> 8) & 255), e1_ = mapa(bar + B_AG2, (c.ranks >> 8) & 255);
  const uint32_t d2 = mapa(ma + 4 * c.mem_step, (c.ranks >> 16) & 255), e2_ = mapa(bar + B_AG2 + c.hc * 8, (c.ranks >> 16) & 255);
  const uint32_t d3 = mapa(ma + 6 * c.mem_step, c.ranks >> 24), e3_ = mapa(bar + B_AG3, c.ranks >> 24);
  char* const xb = reinterpret_cast<char*>(g_xch) + (tt * 16 + (s & 1) * 2048);
  void* const xw = xb + (size_t)blockIdx.x * 8192;
  const void* const xr1 = xb + (size_t)(blockIdx.x ^ 16) * 8192;
  const void* const xr2 = xb + (size_t)(blockIdx.x ^ 32) * 8192;
  const void* const xr3 = xb + (size_t)(blockIdx.x ^ 48) * 8192;
  const uint32_t tag = (s + 1) & 15;
  mbar_wait(bar + B_RS, s & 1, t0);
  if (P) PROF(20);
  uint32_t w0 = 0, w1 = 0;
  if (c.act) {
    uint2 r[8];
#pragma unroll
    for (int u = 0; u < 8; u++) r[u] = lds64(c.rs_addr + u * 576);
    float f0 = ((bflo(r[0].x) + bflo(r[1].x)) + (bflo(r[2].x) + bflo(r[3].x))) + ((bflo(r[4].x) + bflo(r[5].x)) + (bflo(r[6].x) + bflo(r[7].x)));
    float f1 = ((bfhi(r[0].x) + bfhi(r[1].x)) + (bfhi(r[2].x) + bfhi(r[3].x))) + ((bfhi(r[4].x) + bfhi(r[5].x)) + (bfhi(r[6].x) + bfhi(r[7].x)));
    float f2 = ((bflo(r[0].y) + bflo(r[1].y)) + (bflo(r[2].y) + bflo(r[3].y))) + ((bflo(r[4].y) + bflo(r[5].y)) + (bflo(r[6].y) + bflo(r[7].y)));
    float f3 = ((bfhi(r[0].y) + bfhi(r[1].y)) + (bfhi(r[2].y) + bfhi(r[3].y))) + ((bfhi(r[4].y) + bfhi(r[5].y)) + (bfhi(r[6].y) + bfhi(r[7].y)));
    const uint32_t m0 = (__float_as_uint(f0) & ~15u) | tag;
    st_b128(xw, m0, __float_as_uint(f1), __float_as_uint(f2), __float_as_uint(f3));
    if (P) PROF(21);
    uint4 e1, e2, e3;
    while (true) {
      e1 = ld_b128(xr1); e2 = ld_b128(xr2); e3 = ld_b128(xr3);
      if ((((e1.x ^ tag) | (e2.x ^ tag) | (e3.x ^ tag)) & 15u) == 0) break;
      if (timed_out(t0)) break;
    }
    if (P) PROF(22);
    f0 = (__uint_as_float(m0) + __uint_as_float(e1.x)) + (__uint_as_float(e2.x) + __uint_as_float(e3.x));
    f1 = (f1 + __uint_as_float(e1.y)) + (__uint_as_float(e2.y) + __uint_as_float(e3.y));
    f2 = (f2 + __uint_as_float(e1.z)) + (__uint_as_float(e2.z) + __uint_as_float(e3.z));
    f3 = (f3 + __uint_as_float(e1.w)) + (__uint_as_float(e2.w) + __uint_as_float(e3.w));
    w0 = pack2(f0, f1); w1 = pack2(f2, f3);
    sts64(c.mem_addr + c.hc * 8, w0, w1);
  }
  __syncwarp();
  const uint32_t n0 = __shfl_xor_sync(0xffffffffu, w0, 1), n1 = __shfl_xor_sync(0xffffffffu, w1, 1);
  if (lane == 0) mbar_arrive(bar + B_AG0);
  if (c.act) {
    const uint32_t y0 = c.hc ? n0 : w0, y1 = c.hc ? n1 : w1, y2 = c.hc ? w0 : n0, y3 = c.hc ? w1 : n1;
    st_async16(d0, y0, y1, y2, y3, e0);
    st_async16(d1, y0, y1, y2, y3, e1_);
    st_async16(d2, y0, y1, y2, y3, e2_);
    if (!c.hc) st_async16(d3, y0, y1, y2, y3, e3_);
  }
  __syncwarp();
  if (P) PROF(23);
}

__global__ void __launch_bounds__(NTHREADS, 1)
chain_kernel(const bf16* __restrict__ mem0, const bf16* __restrict__ Wq, const bf16* __restrict__ Wk,
             const bf16* __restrict__ Wv, const bf16* __restrict__ Wo, uint32_t zero) {
  extern __shared__ __align__(1024) unsigned char smem_raw[];
  const uint32_t sb = smem_u32(smem_raw);
  const int tid = __shfl_sync(0xffffffffu, (int)threadIdx.x, threadIdx.x & 31);
  const int warp = __shfl_sync(0xffffffffu, tid >> 5, 0), lane = tid & 31;
  const int rank = blockIdx.x & 15, cl = blockIdx.x >> 4;
  const int gi = rank >> 1, a = rank & 1, head = cl * 8 + gi;
  const uint32_t t0 = clk32();
  const uint32_t bar = sb + SM_BAR;
  const uint32_t sl = sb + lane * 16;

  if (tid == 0) {
    atomicAdd(&g_resident, 1u);
    mbar_init(bar + B_AG0, 3); mbar_init(bar + B_AG1, 1); mbar_init(bar + B_AG2, 1); mbar_init(bar + B_AG3, 1);
    mbar_init(bar + B_XQK, 1); mbar_init(bar + B_XV, 9); mbar_init(bar + B_RS, 2); mbar_init(bar + B_KV, 1);
    asm volatile("fence.mbarrier_init.release.cluster;" ::: "memory");
    mbar_arrive(bar + B_AG0); mbar_arrive(bar + B_AG0); mbar_arrive(bar + B_AG0);
    mbar_arrive(bar + B_AG1); mbar_arrive(bar + B_AG2); mbar_arrive(bar + B_AG3);
    mbar_expect(bar + B_XQK, 4096); mbar_expect(bar + B_XV, 2048); mbar_expect(bar + B_RS, RS_BYTES);
  }
  if (tid < 288) {
    int idx = tid >> 5, t = lane >> 2, j = lane & 3;
    int p = idx < 8 ? ((gi + idx) & 7) : 8;
    const uint32_t* src = reinterpret_cast<const uint32_t*>(mem0 + t * DM + 288 * a + 32 * p + 2 * j);
    sts128(sb + SM_MEM + tid * 16, src[0], src[4], src[8], src[12]);
  }
  __syncthreads();
  cluster_sync();

  if (warp < 8) {
    asm volatile("setmaxnreg.inc.sync.aligned.u32 %0;" :: "n"(REG_C));
    const int w = warp;
    const uint32_t wreg = sb + SM_W + w * WREG_UNITS * UNIT;
    const uint32_t stg = sb + SM_STG + w * STG_UNITS * UNIT;
    const int ncol = head * DH + w * 16;
    auto kstep_of = [&](int sp) { int idx = sp >> 1; int p = idx < 8 ? ((gi + idx) & 7) : 8; return 2 * p + (sp & 1); };
    auto perm_addr = [&](int u) { return u < STG_UNITS ? stg + u * UNIT : wreg + (u - STG_UNITS) * UNIT; };
    auto load_final = [&](int u) {
      uint32_t dst = wreg + u * UNIT;
      if (u < U_V2) load_unit(dst, (u & 1) ? Wk : Wq, HD, 288 * a + 16 * kstep_of(u >> 1), ncol, lane);
      else if (u < U_WO) load_unit(dst, Wv, HD, 288 * a + 16 * kstep_of(u - U_V2), ncol, lane);
      else { int v = u - U_WO; load_unit(dst, Wo, DM, head * DH + 16 * (v & 7), 288 * a + 32 * w + 16 * (v >> 3), lane); }
    };
    for (int u = 0; u < 2 * (18 - NX); u++) load_unit(perm_addr(u), (u & 1) ? Wk : Wq, HD, 288 * a + 16 * kstep_of(NX + (u >> 1)), ncol, lane);
    for (int u = 0; u < NPV; u++) load_unit(perm_addr(2 * (18 - NX) + u), Wv, HD, 288 * a + 16 * kstep_of(NV2 + u), ncol, lane);
    asm volatile("cp.async.commit_group;" ::: "memory");
    for (int u = NPERM - STG_UNITS; u < WREG_UNITS; u++) load_final(u);
    asm volatile("cp.async.commit_group;" ::: "memory");
    asm volatile("cp.async.wait_group 1;" ::: "memory");
    __syncwarp();
    uint32_t Pqk[18 - NX][2][4], Pv[NPV][4];
#pragma unroll
    for (int u = 0; u < 2 * (18 - NX); u++) ldsm4t(Pqk[u >> 1][u & 1], perm_addr(u) + lane * 16);
#pragma unroll
    for (int u = 0; u < NPV; u++) ldsm4t(Pv[u], perm_addr(2 * (18 - NX) + u) + lane * 16);
    __syncwarp();
    for (int u = 0; u < NPERM - STG_UNITS; u++) load_final(u);
    cp_async_wait_all();
    __syncwarp();
    const uint32_t wl = wreg + lane * 16;
    uint32_t Xqk[NX][2][4];
#pragma unroll
    for (int u = 0; u < 2 * NX; u++) ldsm4t(Xqk[u >> 1][u & 1], wl + u * UNIT);

    const uint32_t partner = rank ^ 1;
    const uint32_t l_qk = sl + w * 512;
    const uint32_t l_v = sb + w * 256 + lane * 8;
    const uint32_t r_xqk = mapa(l_qk + SM_XQK, partner), r_xv = mapa(l_v + SM_XV, partner), r_pbar = mapa(bar, partner);
    const uint32_t r_rs = mapa(sl + SM_RS + gi * 576, 2 * w + a), r_rsbar = mapa(bar + B_RS, 2 * w + a);
    bar_sync(BAR_ALL, NTHREADS);

    for (int s = 0; s < NSEG; s++) {
      const uint32_t par = s & 1;
      float q0[4] = {0.f, 0.f, 0.f, 0.f}, k0[4] = {0.f, 0.f, 0.f, 0.f}, q1[4] = {0.f, 0.f, 0.f, 0.f}, k1[4] = {0.f, 0.f, 0.f, 0.f};
      uint4 B[9];
      uint32_t V2[NV2][4];
      bool ok = false;
#pragma unroll
      for (int idx = 0; idx < 9; idx++) {
        if (idx == 0) mbar_wait(bar + B_AG0, par, t0);
        if (idx == 1 && !ok) mbar_wait(bar + B_AG1, par, t0);
        if (idx == 3 && !ok) mbar_wait(bar + B_AG2, par, t0);
        if (idx == 6 && !ok) mbar_wait(bar + B_AG3, par, t0);
        if (w == 0) { if (idx == 0) { PROF(0); PROFN(24); PROFS(); } if (idx == 1) PROF(1); if (idx == 3) PROF(2); if (idx == 6) PROF(3); }
        if (idx == 0) { B[0] = lds128(sl + SM_MEM);
          ldsm4t(V2[0], wl + (U_V2 + 0) * UNIT); ldsm4t(V2[1], wl + (U_V2 + 1) * UNIT); ldsm4t(V2[2], wl + (U_V2 + 2) * UNIT);
          ok = mbar_try(bar + B_AG1, par); }
        if (idx == 1) { B[1] = lds128(sl + SM_MEM + 1 * 512); B[2] = lds128(sl + SM_MEM + 2 * 512);
          ldsm4t(V2[3], wl + (U_V2 + 3) * UNIT); ldsm4t(V2[4], wl + (U_V2 + 4) * UNIT);
          ok = mbar_try(bar + B_AG2, par); }
        if (idx == 3) { B[3] = lds128(sl + SM_MEM + 3 * 512); B[4] = lds128(sl + SM_MEM + 4 * 512);
          B[5] = lds128(sl + SM_MEM + 5 * 512);
          ldsm4t(V2[5], wl + (U_V2 + 5) * UNIT); ldsm4t(V2[6], wl + (U_V2 + 6) * UNIT);
          ok = mbar_try(bar + B_AG3, par); }
        if (idx == 6) { B[6] = lds128(sl + SM_MEM + 6 * 512); B[7] = lds128(sl + SM_MEM + 7 * 512);
          B[8] = lds128(sl + SM_MEM + 8 * 512);
          ldsm4t(V2[7], wl + (U_V2 + 7) * UNIT); ldsm4t(V2[8], wl + (U_V2 + 8) * UNIT); }
        const int s0 = 2 * idx, s1 = 2 * idx + 1;
        if (s0 < NX) { mma16816(q0, Xqk[s0][0], B[idx].x, B[idx].y); mma16816(k0, Xqk[s0][1], B[idx].x, B[idx].y); }
        else { mma16816(q0, Pqk[s0 - NX][0], B[idx].x, B[idx].y); mma16816(k0, Pqk[s0 - NX][1], B[idx].x, B[idx].y); }
        if (s1 < NX) { mma16816(q1, Xqk[s1][0], B[idx].z, B[idx].w); mma16816(k1, Xqk[s1][1], B[idx].z, B[idx].w); }
        else { mma16816(q1, Pqk[s1 - NX][0], B[idx].z, B[idx].w); mma16816(k1, Pqk[s1 - NX][1], B[idx].z, B[idx].w); }
      }
      const uint32_t pq0 = pack2(q0[0] + q1[0], q0[1] + q1[1]);
      {
        uint32_t c0 = movmat(pq0), c1 = movmat(pack2(q0[2] + q1[2], q0[3] + q1[3]));
        uint32_t c2 = movmat(pack2(k0[0] + k1[0], k0[1] + k1[1])), c3 = movmat(pack2(k0[2] + k1[2], k0[3] + k1[3]));
        st_async16(r_xqk, c0, c1, c2, c3, r_pbar + B_XQK);
        sts128(l_qk + SM_OQK, c0, c1, c2, c3);
        bar_arrive(BAR_OQK, NTHREADS);
      }
      if (w == 0) PROF(4);
      const float vz = __uint_as_float(pq0 & zero);
      float v[4][4] = {{vz, 0.f, 0.f, 0.f}, {vz, 0.f, 0.f, 0.f}, {vz, 0.f, 0.f, 0.f}, {vz, 0.f, 0.f, 0.f}};
      uint32_t WO[16][4];
#pragma unroll
      for (int idx = 0; idx < 9; idx++) {
        const int s0 = 2 * idx, s1 = 2 * idx + 1;
        if (s0 < NV2) mma16816(v[s0 & 3], V2[s0], B[idx].x, B[idx].y); else mma16816(v[s0 & 3], Pv[s0 - NV2], B[idx].x, B[idx].y);
        if (s1 < NV2) mma16816(v[s1 & 3], V2[s1], B[idx].z, B[idx].w); else mma16816(v[s1 & 3], Pv[s1 - NV2], B[idx].z, B[idx].w);
        if (idx == 3 || idx == 5 || idx == 7) ldsm4t(WO[(idx - 3) >> 1], wl + (U_WO + ((idx - 3) >> 1)) * UNIT);
      }
      {
        const uint32_t vo0 = pack2((v[0][0] + v[1][0]) + (v[2][0] + v[3][0]), (v[0][1] + v[1][1]) + (v[2][1] + v[3][1]));
        const uint32_t vo1 = pack2((v[0][2] + v[1][2]) + (v[2][2] + v[3][2]), (v[0][3] + v[1][3]) + (v[2][3] + v[3][3]));
        st_async8(r_xv, vo0, vo1, r_pbar + B_XV);
        sts64(l_v + SM_OV, vo0, vo1);
        __syncwarp();
        if (lane == 0) mbar_arrive(bar + B_XV);
      }
      if (w == 0) PROF(5);
      if (s == NSEG - 1) break;
#pragma unroll
      for (int u = 3; u < 16; u++) ldsm4t(WO[u], dep(wl, WO[u - PACE][0], zero) + (U_WO + u) * UNIT);
      if (w == 0) PROF(6);
      bar_sync(BAR_O, NTHREADS);
      {
        float m0[4] = {0.f, 0.f, 0.f, 0.f}, m1[4] = {0.f, 0.f, 0.f, 0.f}, m2[4] = {0.f, 0.f, 0.f, 0.f}, m3[4] = {0.f, 0.f, 0.f, 0.f};
        uint4 ob[4];
#pragma unroll
        for (int u = 0; u < 4; u++) ob[u] = lds128(sl + SM_O + u * 512);
#pragma unroll
        for (int u = 0; u < 4; u++) {
          mma16816(m0, WO[2 * u], ob[u].x, ob[u].y);     mma16816(m1, WO[8 + 2 * u], ob[u].x, ob[u].y);
          mma16816(m2, WO[2 * u + 1], ob[u].z, ob[u].w); mma16816(m3, WO[8 + 2 * u + 1], ob[u].z, ob[u].w);
        }
        uint32_t c0 = movmat(pack2(m0[0] + m2[0], m0[1] + m2[1])), c1 = movmat(pack2(m0[2] + m2[2], m0[3] + m2[3]));
        uint32_t c2 = movmat(pack2(m1[0] + m3[0], m1[1] + m3[1])), c3 = movmat(pack2(m1[2] + m3[2], m1[3] + m3[3]));
        if (w == gi) {
          sts128(sl + SM_RS + gi * 576, c0, c1, c2, c3);
          __syncwarp();
          if (lane == 0) mbar_arrive(bar + B_RS);
        } else {
          st_async16(r_rs, c0, c1, c2, c3, r_rsbar);
        }
      }
      if (w == 0) PROF(10);
#pragma unroll
      for (int u = 0; u < 2 * NX; u++)
        ldsm4t(Xqk[u >> 1][u & 1], (u < PACE ? wl : dep(wl, Xqk[(u - PACE) >> 1][(u - PACE) & 1][0], zero)) + u * UNIT);
      if (w == 0) PROF(11);
    }
    __syncwarp();
    cluster_sync();
  } else {
    asm volatile("setmaxnreg.dec.sync.aligned.u32 %0;" :: "n"(REG_A));
    const int x = warp - 8;
    const int g = lane >> 2, j = lane & 3;
    const uint32_t sa = sb + SM_S + x * 512 + (32 * j + 4 * (g >> 1) + (g & 1)) * 4;
    if (x < 2) {
      for (int u = 0; u < 8; u++) load_unit(sb + SM_WOX + (x * 8 + u) * UNIT, Wo, DM, head * DH + 16 * u, 288 * a + 256 + 16 * x, lane);
      cp_async_wait_all();
      __syncwarp();
      bar_sync(BAR_ALL, NTHREADS);
      for (int s = 0; s < NSEG - 1; s++) {
        const uint32_t par = s & 1;
        uint4 R[8];
        mbar_wait(bar + B_KV, par, t0);
#pragma unroll
        for (int u = 0; u < 8; u++) R[u] = lds128(sl + SM_KX + x * 4096 + u * 512);
        float c0[4] = {0.f, 0.f, 0.f, 0.f}, c1[4] = {0.f, 0.f, 0.f, 0.f}, c2[4] = {0.f, 0.f, 0.f, 0.f}, c3[4] = {0.f, 0.f, 0.f, 0.f};
        bar_sync(BAR_OQK, NTHREADS);
        {
          uint2 b[8];
#pragma unroll
          for (int u = 0; u < 8; u++) b[u] = lds64(sl + SM_OQK + u * 512);
          mmaq(c0, R[0], b[0].x, b[0].y); mmaq(c1, R[1], b[1].x, b[1].y); mmaq(c2, R[2], b[2].x, b[2].y); mmaq(c3, R[3], b[3].x, b[3].y);
          mmaq(c0, R[4], b[4].x, b[4].y); mmaq(c1, R[5], b[5].x, b[5].y); mmaq(c2, R[6], b[6].x, b[6].y); mmaq(c3, R[7], b[7].x, b[7].y);
        }
        if (x == 0) PROF(16);
        mbar_wait(bar + B_XQK, par, t0);
        if (x == 0) PROF(17);
        {
          uint2 b[8];
#pragma unroll
          for (int u = 0; u < 8; u++) b[u] = lds64(sl + SM_XQK + u * 512);
          mmaq(c0, R[0], b[0].x, b[0].y); mmaq(c1, R[1], b[1].x, b[1].y); mmaq(c2, R[2], b[2].x, b[2].y); mmaq(c3, R[3], b[3].x, b[3].y);
          mmaq(c0, R[4], b[4].x, b[4].y); mmaq(c1, R[5], b[5].x, b[5].y); mmaq(c2, R[6], b[6].x, b[6].y); mmaq(c3, R[7], b[7].x, b[7].y);
        }
        sts32(sa, __float_as_uint((c0[0] + c1[0]) + (c2[0] + c3[0])));
        sts32(sa + 64, __float_as_uint((c0[1] + c1[1]) + (c2[1] + c3[1])));
        sts32(sa + 8, __float_as_uint((c0[2] + c1[2]) + (c2[2] + c3[2])));
        sts32(sa + 72, __float_as_uint((c0[3] + c1[3]) + (c2[3] + c3[3])));
        if (x == 0) PROF(18);
        softmax_pv(s, x, sb, sl, bar, lane, a, head, t0, x == 0);
        uint32_t WX[8][4];
#pragma unroll
        for (int u = 0; u < 8; u++) ldsm4t(WX[u], sl + SM_WOX + (x * 8 + u) * UNIT);
        const int ln = opaque(lane);
        const uint32_t r_rs2 = mapa(sb + SM_RS + gi * 576 + (32 + (ln & 3)) * 16 + x * 8, 2 * (ln >> 2) + a), r_rsb2 = mapa(bar + B_RS, 2 * (ln >> 2) + a);
        bar_sync(BAR_O, NTHREADS);
        {
          float m0[4] = {0.f, 0.f, 0.f, 0.f}, m1[4] = {0.f, 0.f, 0.f, 0.f};
          uint4 ob[4];
#pragma unroll
          for (int u = 0; u < 4; u++) ob[u] = lds128(sl + SM_O + u * 512);
#pragma unroll
          for (int u = 0; u < 4; u++) { mma16816(m0, WX[2 * u], ob[u].x, ob[u].y); mma16816(m1, WX[2 * u + 1], ob[u].z, ob[u].w); }
          uint32_t d0 = movmat(pack2(m0[0] + m1[0], m0[1] + m1[1])), d1 = movmat(pack2(m0[2] + m1[2], m0[3] + m1[3]));
          st_async8(r_rs2, d0, d1, r_rsb2);
        }
        if (x == 0) PROF(19);
        reduce_exchange(x, gi, a, s, sb, bar, lane, t0, x == 0);
      }
      bar_sync(BAR_OQK, NTHREADS);
    } else {
      const unsigned epoch = g_epoch + 1;
      const uint4* kx_g = g_Kf + (size_t)head * 128 * 256;
      const uint4* vx_g = g_Vf + (size_t)head * NSEG * 512;
      const int hh = x - 2;
      const uint32_t sm_ = sa - hh * 512 + hh * 8;
      uint4* const km_ptr = g_Kmf + (size_t)head * NSEG * 128 + hh * 64 + lane;
      if (x == 3 && lane == 0) {
        while (ld_acquire(&g_kvflag[head]) != epoch) { if (timed_out(t0)) break; }
        while (ld_acquire(&g_kvflag[32 + head]) != epoch) { if (timed_out(t0)) break; }
        asm volatile("fence.proxy.async.global;" ::: "memory");
      }
      __syncwarp();
      bar_sync(BAR_ALL, NTHREADS);
      if (x == 3 && lane == 0) {
        mbar_expect(bar + B_KV, 16384);
        bulk_g2s(sb + SM_KX, kx_g, 8192, bar + B_KV);
        bulk_g2s(sb + SM_VX, vx_g, 8192, bar + B_KV);
      }
      __syncwarp();
      for (int s = 0; s < NSEG; s++) {
        const uint32_t par = s & 1;
        uint4 R[4], o[4];
        if (s < NSEG - 1) mbar_wait(bar + B_KV, par, t0);
        bar_sync(BAR_OQK, NTHREADS);
#pragma unroll
        for (int u = 0; u < 4; u++) R[u] = lds128(sl + SM_OQK + (hh * 4 + u) * 512);
        mbar_wait(bar + B_XQK, par, t0);
        float c0[4] = {0.f, 0.f, 0.f, 0.f}, c1[4] = {0.f, 0.f, 0.f, 0.f}, c2[4] = {0.f, 0.f, 0.f, 0.f}, c3[4] = {0.f, 0.f, 0.f, 0.f};
#pragma unroll
        for (int u = 0; u < 4; u++) o[u] = lds128(sl + SM_XQK + (hh * 4 + u) * 512);
#pragma unroll
        for (int u = 0; u < 4; u++) {
          uint4& r = R[u];
          r.x = hadd2bf(r.x, o[u].x); r.y = hadd2bf(r.y, o[u].y); r.z = hadd2bf(r.z, o[u].z); r.w = hadd2bf(r.w, o[u].w);
        }
#pragma unroll
        for (int u = 0; u < 4; u += 2) {
          mma1688(c0, R[u].z, R[u].w, R[u].x);
          mma1688(c1, R[u].z, R[u].w, R[u].y);
          mma1688(c2, R[u + 1].z, R[u + 1].w, R[u + 1].x);
          mma1688(c3, R[u + 1].z, R[u + 1].w, R[u + 1].y);
        }
        sts32(sm_, __float_as_uint((c0[0] + c1[2]) + (c2[0] + c3[2])));
        sts32(sm_ + 64, __float_as_uint((c0[1] + c1[3]) + (c2[1] + c3[3])));
        if (a == 0) {
          km_ptr[(size_t)s * 128] = make_uint4(R[0].z, R[0].w, R[1].z, R[1].w);
          km_ptr[(size_t)s * 128 + 32] = make_uint4(R[2].z, R[2].w, R[3].z, R[3].w);
        }
        if (s == NSEG - 1) break;
        softmax_pv(s, x, sb, sl, bar, lane, a, head, t0, 0);
        bar_sync(BAR_O, NTHREADS);
        if (x == 2) {
          reduce_exchange(x, gi, a, s, sb, bar, lane, t0, 0);
          if (lane == 0) mbar_expect(bar + B_RS, RS_BYTES);
        } else if (lane == 0) {
          if (s + 1 < NSEG - 1) {
            mbar_expect(bar + B_KV, 16384);
            bulk_g2s(sb + SM_KX, kx_g + (size_t)(s + 1) * 512, 8192, bar + B_KV);
            bulk_g2s(sb + SM_VX, vx_g + (size_t)(s + 1) * 512, 8192, bar + B_KV);
          }
          mbar_expect(bar + B_AG1, AG1_BYTES); mbar_expect(bar + B_AG2, AG2_BYTES); mbar_expect(bar + B_AG3, AG3_BYTES);
          mbar_expect(bar + B_XQK, 4096); mbar_expect(bar + B_XV, 2048);
          if (a == 0 && (s & 3) == 3) st_release(&g_memflag[head * 8], epoch * 64 + s + 1);
          if ((s & 3) == 2 && s + 2 < NSEG) {
            while (ld_acquire(&g_kvflag[((s + 2) >> 2) * 64 + head]) != epoch) { if (timed_out(t0)) break; }
            while (ld_acquire(&g_kvflag[((s + 2) >> 2) * 64 + 32 + head]) != epoch) { if (timed_out(t0)) break; }
            asm volatile("fence.proxy.async.global;" ::: "memory");
          }
        }
        __syncwarp();
      }
    }
    {
      mbar_wait(bar + B_XV, (NSEG - 1) & 1, t0);
      const uint32_t lv = sb + x * 512 + lane * 8;
      const uint2 ov0 = lds64(lv + SM_OV), xv0 = lds64(lv + SM_XV), ov1 = lds64(lv + SM_OV + 256), xv1 = lds64(lv + SM_XV + 256);
      if (a == 0) g_Vmf[((size_t)head * NSEG + NSEG - 1) * 128 + x * 32 + lane] = make_uint4(hadd2bf(ov0.x, xv0.x), hadd2bf(ov0.y, xv0.y), hadd2bf(ov1.x, xv1.x), hadd2bf(ov1.y, xv1.y));
      bar_sync(BAR_S, 128);
      if (x == 3 && a == 0 && lane == 0) st_release(&g_memflag[head * 8], (g_epoch + 1) * 64 + 64);
    }
    __syncwarp();
    cluster_sync();
  }
}
}
__device__ __align__(1024) uint4 g_xnT[NRB * 9 * 1024];
__device__ __align__(1024) uint4 g_hnT[NRB * 9 * 1024];
__device__ __align__(1024) uint4 g_oT[NRB * 64 * 1024];
__device__ __align__(1024) uint4 g_gT[NRB * 72 * 1024];
constexpr int MAXSPLIT = 8;
__device__ __align__(1024) uint4 g_p1[MAXSPLIT * 256 * 18 * 32];
__device__ __align__(1024) uint4 g_p2[MAXSPLIT * 256 * 18 * 32];
__device__ __align__(1024) uint4 g_hT[256 * 18 * 32];

__global__ void __launch_bounds__(192) ln1_kernel(const bf16* __restrict__ x) {
  __shared__ float red[2][6][8];
  if (blockIdx.x != 0) asm volatile("griddepcontrol.launch_dependents;");
  const int r8 = blockIdx.x, w = threadIdx.x >> 5, lane = threadIdx.x & 31, g = lane >> 2, j = lane & 3;
  const uint4* src = reinterpret_cast<const uint4*>(x + (size_t)(r8 * 8 + g) * DM) + w * 12 + j;
  uint4 v[3];
#pragma unroll
  for (int t = 0; t < 3; t++) v[t] = src[t * 4];
  float f[24];
#pragma unroll
  for (int t = 0; t < 3; t++) {
    f[t * 8 + 0] = bflo(v[t].x); f[t * 8 + 1] = bfhi(v[t].x); f[t * 8 + 2] = bflo(v[t].y); f[t * 8 + 3] = bfhi(v[t].y);
    f[t * 8 + 4] = bflo(v[t].z); f[t * 8 + 5] = bfhi(v[t].z); f[t * 8 + 6] = bflo(v[t].w); f[t * 8 + 7] = bfhi(v[t].w);
  }
  float s = 0.f;
#pragma unroll
  for (int i = 0; i < 24; i++) s += f[i];
  s += __shfl_xor_sync(~0u, s, 1); s += __shfl_xor_sync(~0u, s, 2);
  if (j == 0) red[0][w][g] = s;
  __syncthreads();
  const float mean = (red[0][0][g] + red[0][1][g] + red[0][2][g] + red[0][3][g] + red[0][4][g] + red[0][5][g]) * (1.f / DM);
  float q = 0.f;
#pragma unroll
  for (int i = 0; i < 24; i++) { f[i] -= mean; q += f[i] * f[i]; }
  q += __shfl_xor_sync(~0u, q, 1); q += __shfl_xor_sync(~0u, q, 2);
  if (j == 0) red[1][w][g] = q;
  __syncthreads();
  const float var = (red[1][0][g] + red[1][1][g] + red[1][2][g] + red[1][3][g] + red[1][4][g] + red[1][5][g]) * (1.f / DM);
  const float rs = rsqrtf(var + 1e-5f);
#pragma unroll
  for (int t = 0; t < 3; t++) {
    const int c = w * 12 + t * 4 + j;
    uint4* dst = g_xnT + ((size_t)(r8 >> 4) * 9 + (c >> 3)) * 1024 + (r8 & 15) * 64 + (c & 7) * 8 + g;
    *dst = make_uint4(pack2(f[t * 8] * rs, f[t * 8 + 1] * rs), pack2(f[t * 8 + 2] * rs, f[t * 8 + 3] * rs),
                      pack2(f[t * 8 + 4] * rs, f[t * 8 + 5] * rs), pack2(f[t * 8 + 6] * rs, f[t * 8 + 7] * rs));
  }
  if (blockIdx.x == 0 && threadIdx.x == 0) {
    const uint32_t t0 = clk32();
    const unsigned need = (g_epoch + 1) * 64u;
    while ((int)(ld_acquire(&g_resident) - need) < 0) { if (timed_out(t0)) break; __nanosleep(100); }
  }
}

template <int S>
__global__ void __launch_bounds__(192) ln2_kernel(const bf16* __restrict__ x, int r8_base) {
  __shared__ float red[2][6][8];
  asm volatile("griddepcontrol.launch_dependents;");
  const int r8 = blockIdx.x + r8_base, w = threadIdx.x >> 5, lane = threadIdx.x & 31, g = lane >> 2, j = lane & 3;
  const uint32_t* xs = reinterpret_cast<const uint32_t*>(x + (size_t)(r8 * 8 + g) * DM) + w * 48 + j;
  uint32_t xv[12];
#pragma unroll
  for (int i = 0; i < 12; i++) xv[i] = xs[i * 4];
  asm volatile("griddepcontrol.wait;" ::: "memory");
  float f[24];
#pragma unroll
  for (int i = 0; i < 24; i++) f[i] = 0.f;
  const uint4* p = g_p1 + ((size_t)r8 * 18 + w * 3) * 32 + lane;
#pragma unroll
  for (int s = 0; s < S; s++) {
#pragma unroll
    for (int t = 0; t < 3; t++) {
      const uint4 v = ldg_cg(p + (size_t)s * 256 * 18 * 32 + t * 32);
      f[t * 8 + 0] += bflo(v.x); f[t * 8 + 1] += bfhi(v.x); f[t * 8 + 2] += bflo(v.y); f[t * 8 + 3] += bfhi(v.y);
      f[t * 8 + 4] += bflo(v.z); f[t * 8 + 5] += bfhi(v.z); f[t * 8 + 6] += bflo(v.w); f[t * 8 + 7] += bfhi(v.w);
    }
  }
  uint32_t hp[12];
  float s = 0.f;
#pragma unroll
  for (int i = 0; i < 12; i++) {
    hp[i] = pack2(f[2 * i] + bflo(xv[i]), f[2 * i + 1] + bfhi(xv[i]));
    f[2 * i] = bflo(hp[i]); f[2 * i + 1] = bfhi(hp[i]);
    s += f[2 * i] + f[2 * i + 1];
  }
#pragma unroll
  for (int t = 0; t < 3; t++) g_hT[((size_t)r8 * 18 + w * 3 + t) * 32 + lane] = make_uint4(hp[4 * t], hp[4 * t + 1], hp[4 * t + 2], hp[4 * t + 3]);
  s += __shfl_xor_sync(~0u, s, 1); s += __shfl_xor_sync(~0u, s, 2);
  if (j == 0) red[0][w][g] = s;
  __syncthreads();
  const float mean = (red[0][0][g] + red[0][1][g] + red[0][2][g] + red[0][3][g] + red[0][4][g] + red[0][5][g]) * (1.f / DM);
  float q = 0.f;
#pragma unroll
  for (int i = 0; i < 24; i++) { f[i] -= mean; q += f[i] * f[i]; }
  q += __shfl_xor_sync(~0u, q, 1); q += __shfl_xor_sync(~0u, q, 2);
  if (j == 0) red[1][w][g] = q;
  __syncthreads();
  const float var = (red[1][0][g] + red[1][1][g] + red[1][2][g] + red[1][3][g] + red[1][4][g] + red[1][5][g]) * (1.f / DM);
  const float rs = rsqrtf(var + 1e-5f);
#pragma unroll
  for (int t = 0; t < 3; t++) {
    const int u = w * 3 + t;
    uint4* dst = g_hnT + ((size_t)(r8 >> 4) * 9 + (u >> 1)) * 1024 + (r8 & 15) * 64 + ((u & 1) * 4 + j) * 8 + g;
    *dst = make_uint4(pack2(f[t * 8] * rs, f[t * 8 + 1] * rs), pack2(f[t * 8 + 2] * rs, f[t * 8 + 3] * rs),
                      pack2(f[t * 8 + 4] * rs, f[t * 8 + 5] * rs), pack2(f[t * 8 + 6] * rs, f[t * 8 + 7] * rs));
  }
}

template <int S>
__global__ void __launch_bounds__(192) fin_kernel(const bf16* __restrict__ b2, bf16* __restrict__ out, int r8_base, int last) {
  const int r8 = blockIdx.x + r8_base, w = threadIdx.x >> 5, lane = threadIdx.x & 31, g = lane >> 2, j = lane & 3;
  const uint32_t* bs = reinterpret_cast<const uint32_t*>(b2) + w * 48 + j;
  float f[24];
#pragma unroll
  for (int i = 0; i < 12; i++) { const uint32_t b = bs[i * 4]; f[2 * i] = bflo(b); f[2 * i + 1] = bfhi(b); }
  asm volatile("griddepcontrol.wait;" ::: "memory");
  const uint4* p = g_p2 + ((size_t)r8 * 18 + w * 3) * 32 + lane;
#pragma unroll
  for (int s = 0; s < S; s++) {
#pragma unroll
    for (int t = 0; t < 3; t++) {
      const uint4 v = ldg_cg(p + (size_t)s * 256 * 18 * 32 + t * 32);
      f[t * 8 + 0] += bflo(v.x); f[t * 8 + 1] += bfhi(v.x); f[t * 8 + 2] += bflo(v.y); f[t * 8 + 3] += bfhi(v.y);
      f[t * 8 + 4] += bflo(v.z); f[t * 8 + 5] += bfhi(v.z); f[t * 8 + 6] += bflo(v.w); f[t * 8 + 7] += bfhi(v.w);
    }
  }
  uint32_t* o = reinterpret_cast<uint32_t*>(out + (size_t)(r8 * 8 + g) * DM) + w * 48 + j;
#pragma unroll
  for (int t = 0; t < 3; t++) {
    const uint4 h = ldg_cg(g_hT + ((size_t)r8 * 18 + w * 3 + t) * 32 + lane);
    o[(t * 4 + 0) * 4] = pack2(f[t * 8 + 0] + bflo(h.x), f[t * 8 + 1] + bfhi(h.x));
    o[(t * 4 + 1) * 4] = pack2(f[t * 8 + 2] + bflo(h.y), f[t * 8 + 3] + bfhi(h.y));
    o[(t * 4 + 2) * 4] = pack2(f[t * 8 + 4] + bflo(h.z), f[t * 8 + 5] + bfhi(h.z));
    o[(t * 4 + 3) * 4] = pack2(f[t * 8 + 6] + bflo(h.w), f[t * 8 + 7] + bfhi(h.w));
  }
  if (last && blockIdx.x == 0 && threadIdx.x == 0) g_epoch = g_epoch + 1;
}

namespace bres {
constexpr int NS = 5;
constexpr int SM_B = 0, SM_A = 9 * 16384, SM_BAR = SM_A + NS * 16384, SM_TOTAL = SM_BAR + 256;
enum { M_KV = 0, M_QA = 1, M_F1 = 2 };
template <bool B> struct BoolC { static constexpr bool value = B; };

__device__ __forceinline__ float gelu_tanh(float z) {
  const float u = z * fmaf(z * z, 0.044715f * 0.7978845608028654f, 0.7978845608028654f);
  float t; asm("tanh.approx.f32 %0, %1;" : "=f"(t) : "f"(u));
  const float hz = 0.5f * z;
  return fmaf(hz, t, hz);
}

template <int MODE>
__global__ void __launch_bounds__(384, 1)
bres_kernel(const __grid_constant__ CUtensorMap mapB0, const __grid_constant__ CUtensorMap mapB1, const bf16* __restrict__ bias,
            int nslice, int rb0, int rb_step, int ntile_in) {
  extern __shared__ __align__(1024) unsigned char smem_raw[];
  const uint32_t sb = smem_u32(smem_raw);
  const int tid = threadIdx.x, wg = tid >> 7, lane = tid & 31, w = (tid >> 5) & 3;
  const uint32_t bar = sb + SM_BAR;
  const uint32_t t0 = clk32();
  const int slice = blockIdx.x % nslice, part = blockIdx.x / nslice;
  const int rbs = rb0 + part;
  const int ntile = ntile_in >= 0 ? ntile_in : (NRB - rbs + rb_step - 1) / rb_step;
  if (tid == 0) {
    for (int i = 0; i < NS; i++) { mbar_init(bar + i * 8, 1); mbar_init(bar + (NS + i) * 8, 4); }
    for (int i = 0; i < 9; i++) mbar_init(bar + (2 * NS + i) * 8, 1);
    asm volatile("fence.mbarrier_init.release.cluster;" ::: "memory");
  }
  __syncthreads();
  asm volatile("griddepcontrol.launch_dependents;");
  if (wg == 2) {
    asm volatile("setmaxnreg.dec.sync.aligned.u32 40;");
    if (tid == 256) {
      const bool isV = MODE == M_KV && slice >= 32;
      const CUtensorMap* mb = isV ? &mapB1 : &mapB0;
      const int col = (slice & (MODE == M_KV ? 31 : 0xffff)) * 128;
      for (int kb = 0; kb < 9; kb++) {
        const uint32_t fb = bar + (2 * NS + kb) * 8;
        mbar_expect(fb, 16384);
        if (MODE == M_F1) { tma5d(sb + SM_B + kb * 16384, mb, col, kb * 2, fb); tma5d(sb + SM_B + kb * 16384 + 8192, mb, col + 64, kb * 2, fb); }
        else { tma2d(sb + SM_B + kb * 16384, mb, col, kb * 64, fb); tma2d(sb + SM_B + kb * 16384 + 8192, mb, col + 64, kb * 64, fb); }
      }
      asm volatile("griddepcontrol.wait;" ::: "memory");
      const uint4* A = MODE == M_F1 ? g_hnT : g_xnT;
      int st = 0, ph = 1;
      for (int t = 0; t < ntile; t++) {
        const uint4* src = A + (size_t)(rbs + t * rb_step) * 9 * 1024;
        for (int kb = 0; kb < 9; kb++) {
          mbar_wait(bar + (NS + st) * 8, ph, t0);
          mbar_expect(bar + st * 8, 16384);
          bulk_g2s(sb + SM_A + st * 16384, src + kb * 1024, 16384, bar + st * 8);
          if (++st == NS) { st = 0; ph ^= 1; }
        }
      }
    }
  } else {
    asm volatile("setmaxnreg.inc.sync.aligned.u32 232;");
    asm volatile("griddepcontrol.wait;" ::: "memory");
    const bool isV = MODE == M_KV && slice >= 32;
    const int g = lane >> 2, j = lane & 3;
    const unsigned epoch = g_epoch + 1;
    for (int t = wg; t < ntile; t += 2) {
      const int rb = rbs + t * rb_step;
      float acc[2][64];
      int it = t * 9, st = it % NS, ph = (it / NS) & 1, prev = -1;
      uint4 kf[16];
      if (MODE == M_QA) {
        const uint4* kp = g_Kf + ((size_t)slice * 128 + rb * 8 + w * 2) * 256 + lane;
#pragma unroll
        for (int i = 0; i < 16; i++) kf[i] = ldg_cg(kp + i * 32);
      }
      if (t > 0) bar_sync(3 + wg, 256);
      auto mainloop = [&](auto trans) {
        constexpr bool TR = decltype(trans)::value;
        for (int kb = 0; kb < 9; kb++) {
          if (t < 2) mbar_wait(bar + (2 * NS + kb) * 8, 0, t0);
          mbar_wait(bar + st * 8, ph, t0);
          const uint32_t aaddr = sb + SM_A + st * 16384, baddr = sb + SM_B + kb * 16384;
          wg_fence();
#pragma unroll
          for (int ks = 0; ks < 4; ks++) {
            if (TR) {
              const uint64_t dx = make_desc(aaddr + ks * 256, 128, 1024, 0);
              wgmma_n128<1, 0>(acc[0], make_desc(baddr + ks * 2048, 8192, 1024, 1), dx, (kb | ks) != 0);
              wgmma_n128<1, 0>(acc[1], make_desc(baddr + 8192 + ks * 2048, 8192, 1024, 1), dx, (kb | ks) != 0);
            } else {
              const uint64_t dw = make_desc(baddr + ks * 2048, 8192, 1024, 1);
              if (MODE == M_QA) {
                wgmma_n128<0, 1>(acc[0], make_desc(aaddr + ks * 256, 128, 2048, 0), dw, (kb | ks) != 0);
                wgmma_n128<0, 1>(acc[1], make_desc(aaddr + 1024 + ks * 256, 128, 2048, 0), dw, (kb | ks) != 0);
              } else {
                wgmma_n128<0, 1>(acc[0], make_desc(aaddr + ks * 256, 128, 1024, 0), dw, (kb | ks) != 0);
                wgmma_n128<0, 1>(acc[1], make_desc(aaddr + 8192 + ks * 256, 128, 1024, 0), dw, (kb | ks) != 0);
              }
            }
          }
          wg_commit();
          if (kb == 8 && t + 1 < ntile) bar_arrive(3 + (wg ^ 1), 256);
          if (prev >= 0) { wg_wait<1>(); if (lane == 0) mbar_arrive(bar + (NS + prev) * 8); }
          prev = st;
          if (++st == NS) { st = 0; ph ^= 1; }
        }
        wg_wait<0>();
      };
      if (isV) mainloop(BoolC<true>()); else mainloop(BoolC<false>());
      if (lane == 0) mbar_arrive(bar + (NS + prev) * 8);
      fence_regs(acc[0]); fence_regs(acc[1]);
      if (MODE == M_KV) {
        const int head = slice & 31;
#pragma unroll
        for (int mb = 0; mb < 2; mb++) {
#pragma unroll
          for (int q = 0; q < 8; q++) {
            uint4* dst = isV ? g_Vf + ((((size_t)head * NSEG + rb * 4 + (q >> 1)) * 8 + mb * 4 + w) * 2 + (q & 1)) * 32 + lane
                             : g_Kf + (((size_t)head * 128 + rb * 8 + mb * 4 + w) * 8 + q) * 32 + lane;
            const float* c = &acc[mb][q * 8];
            stg128(dst, pack2(c[0], c[1]), pack2(c[2], c[3]), pack2(c[4], c[5]), pack2(c[6], c[7]));
          }
        }
        bar_sync(1 + wg, 128);
        if (tid == wg * 128) st_release(&g_kvflag[rb * 64 + slice], epoch);
      } else if (MODE == M_F1) {
        const uint32_t* bp = reinterpret_cast<const uint32_t*>(bias + slice * 128) + j;
#pragma unroll
        for (int u = 0; u < 4; u++) {
          float bl[4], bh[4];
#pragma unroll
          for (int i = 0; i < 4; i++) { const uint32_t b = __ldg(bp + (u * 4 + i) * 4); bl[i] = bflo(b); bh[i] = bfhi(b); }
#pragma unroll
          for (int mb = 0; mb < 2; mb++) {
#pragma unroll
            for (int hi = 0; hi < 2; hi++) {
              uint32_t p[4];
#pragma unroll
              for (int i = 0; i < 4; i++) {
                const float* c = &acc[mb][(u * 4 + i) * 4 + hi * 2];
                p[i] = pack2(gelu_tanh(c[0] + bl[i]), gelu_tanh(c[1] + bh[i]));
              }
              uint4* dst = g_gT + ((size_t)rb * 72 + slice * 2 + (u >> 1)) * 1024 + (mb * 8 + w * 2 + hi) * 64 + ((u & 1) * 4 + j) * 8 + g;
              stg128(dst, p[0], p[1], p[2], p[3]);
            }
          }
        }
      } else {
        const int seg = rb * 4 + w;
        uint32_t qa[2][8][4];
#pragma unroll
        for (int mb = 0; mb < 2; mb++)
#pragma unroll
          for (int ks = 0; ks < 8; ks++)
#pragma unroll
            for (int i = 0; i < 4; i++) qa[mb][ks][i] = pack2(acc[mb][ks * 8 + 2 * i], acc[mb][ks * 8 + 2 * i + 1]);
        if (lane == 0) {
          const unsigned need = epoch * 64 + rb * 4 + 4;
          while (ld_acquire(&g_memflag[slice * 8]) < need) { if (timed_out(t0)) break; __nanosleep(200); }
        }
        __syncwarp();
        uint4 km[4], vm[4], vf[16];
        {
          const uint4* kmp = g_Kmf + ((size_t)slice * NSEG + seg) * 128 + lane;
          const uint4* vmp = g_Vmf + ((size_t)slice * NSEG + seg) * 128 + lane;
          const uint4* vp = g_Vf + ((size_t)slice * NSEG + seg) * 512 + lane;
#pragma unroll
          for (int i = 0; i < 4; i++) km[i] = ldg_cg(kmp + i * 32);
#pragma unroll
          for (int i = 0; i < 4; i++) vm[i] = ldg_cg(vmp + i * 32);
#pragma unroll
          for (int i = 0; i < 8; i++) vf[i] = ldg_cg(vp + i * 32);
          float sc[2][5][4];
#pragma unroll
          for (int mb = 0; mb < 2; mb++)
#pragma unroll
            for (int n = 0; n < 5; n++) { sc[mb][n][0] = sc[mb][n][1] = sc[mb][n][2] = sc[mb][n][3] = 0.f; }
#pragma unroll
          for (int ks = 0; ks < 8; ks++) {
#pragma unroll
            for (int mb = 0; mb < 2; mb++) {
              mma16816(sc[mb][0], qa[mb][ks], kf[ks].x, kf[ks].z);
              mma16816(sc[mb][1], qa[mb][ks], kf[ks].y, kf[ks].w);
              mma16816(sc[mb][2], qa[mb][ks], kf[8 + ks].x, kf[8 + ks].z);
              if (mb == 1) mma16816(sc[mb][3], qa[mb][ks], kf[8 + ks].y, kf[8 + ks].w);
            }
          }
#pragma unroll
          for (int i = 8; i < 16; i++) vf[i] = ldg_cg(vp + i * 32);
#pragma unroll
          for (int u = 0; u < 4; u++) {
#pragma unroll
            for (int mb = 0; mb < 2; mb++) {
              mma16816(sc[mb][4], qa[mb][2 * u], km[u].x, km[u].y);
              mma16816(sc[mb][4], qa[mb][2 * u + 1], km[u].z, km[u].w);
            }
          }
          const float scl = 0.08838834764831845f * 1.4426950408889634f;
          const float NEG = -INFINITY;
          uint32_t pa[2][5][2];
          float inv[2][2];
#pragma unroll
          for (int mb = 0; mb < 2; mb++) {
#pragma unroll
            for (int hi = 0; hi < 2; hi++) {
              const int nd = mb + 2 * hi;
              if (2 * j > g) sc[mb][nd][hi * 2] = NEG;
              if (2 * j + 1 > g) sc[mb][nd][hi * 2 + 1] = NEG;
              float m = fmaxf(sc[mb][4][hi * 2], sc[mb][4][hi * 2 + 1]);
#pragma unroll
              for (int n = 0; n < 4; n++) if (n <= nd) m = fmaxf(m, fmaxf(sc[mb][n][hi * 2], sc[mb][n][hi * 2 + 1]));
              m = fmaxf(m, __shfl_xor_sync(~0u, m, 1)); m = fmaxf(m, __shfl_xor_sync(~0u, m, 2));
              const float mc = m * scl;
              float l = 0.f;
#pragma unroll
              for (int n = 0; n < 5; n++) {
                if (n <= nd || n == 4) {
                  const float e0 = ex2(fmaf(sc[mb][n][hi * 2], scl, -mc)), e1 = ex2(fmaf(sc[mb][n][hi * 2 + 1], scl, -mc));
                  l += e0 + e1;
                  pa[mb][n][hi] = pack2(e0, e1);
                } else pa[mb][n][hi] = 0u;
              }
              l += __shfl_xor_sync(~0u, l, 1); l += __shfl_xor_sync(~0u, l, 2);
              inv[mb][hi] = __fdividef(1.f, l);
            }
          }
#pragma unroll
          for (int u = 0; u < 4; u++) {
            float o[2][4][4];
#pragma unroll
            for (int mb = 0; mb < 2; mb++) {
#pragma unroll
              for (int i = 0; i < 4; i++) {
                o[mb][i][0] = o[mb][i][1] = o[mb][i][2] = o[mb][i][3] = 0.f;
                const uint4 v0 = vf[(2 * u + (i >> 1)) * 2], v1 = vf[(2 * u + (i >> 1)) * 2 + 1];
                const uint32_t vmw = i == 0 ? vm[u].x : i == 1 ? vm[u].y : i == 2 ? vm[u].z : vm[u].w;
                mma1688(o[mb][i], pa[mb][4][0], pa[mb][4][1], vmw);
                mma16816(o[mb][i], pa[mb][0][0], pa[mb][0][1], pa[mb][1][0], pa[mb][1][1], (i & 1) ? v0.y : v0.x, (i & 1) ? v0.w : v0.z);
                if (mb == 0) mma1688(o[mb][i], pa[mb][2][0], pa[mb][2][1], (i & 1) ? v1.y : v1.x);
                else mma16816(o[mb][i], pa[mb][2][0], pa[mb][2][1], pa[mb][3][0], pa[mb][3][1], (i & 1) ? v1.y : v1.x, (i & 1) ? v1.w : v1.z);
              }
            }
#pragma unroll
            for (int mb = 0; mb < 2; mb++) {
#pragma unroll
              for (int hi = 0; hi < 2; hi++) {
                const float s = inv[mb][hi];
                uint4* dst = g_oT + ((size_t)rb * 64 + slice * 2 + (u >> 1)) * 1024 + (w * 4 + mb + 2 * hi) * 64 + ((u & 1) * 4 + j) * 8 + g;
                stg128(dst, pack2(o[mb][0][hi * 2] * s, o[mb][0][hi * 2 + 1] * s), pack2(o[mb][1][hi * 2] * s, o[mb][1][hi * 2 + 1] * s),
                       pack2(o[mb][2][hi * 2] * s, o[mb][2][hi * 2 + 1] * s), pack2(o[mb][3][hi * 2] * s, o[mb][3][hi * 2 + 1] * s));
              }
            }
          }
        }
      }
    }
  }
}
}

namespace sk {
constexpr int NS = 4, STAGE = 16384 + 5 * 8192;
constexpr int SM_BAR = NS * STAGE, SM_TOTAL = SM_BAR + 128;
__global__ void __launch_bounds__(384, 1)
sk_kernel(const __grid_constant__ CUtensorMap mapB, const uint4* __restrict__ A, uint4* __restrict__ P, int nkb_total, int S, int rb0) {
  extern __shared__ __align__(1024) unsigned char smem_raw[];
  const uint32_t sb = smem_u32(smem_raw);
  const int tid = threadIdx.x, wg = tid >> 7, lane = tid & 31, w = (tid >> 5) & 3;
  const uint32_t bar = sb + SM_BAR;
  const uint32_t t0 = clk32();
  const int nt = gridDim.x / S;
  const int split = blockIdx.x / nt, tile = blockIdx.x % nt, half = tile & 1, rb = rb0 + (tile >> 1);
  const int nkb = nkb_total / S, kb0 = split * nkb;
  if (tid == 0) {
    for (int i = 0; i < NS; i++) { mbar_init(bar + i * 8, 1); mbar_init(bar + (NS + i) * 8, 8); }
    asm volatile("fence.mbarrier_init.release.cluster;" ::: "memory");
  }
  __syncthreads();
  asm volatile("griddepcontrol.launch_dependents;");
  if (wg == 2) {
    asm volatile("setmaxnreg.dec.sync.aligned.u32 40;");
    if (tid == 256) {
      int st = 0, ph = 1;
      const uint4* src = A + ((size_t)rb * nkb_total + kb0) * 1024;
      for (int kb = 0; kb < nkb; kb++) {
        mbar_wait(bar + (NS + st) * 8, ph, t0);
        const uint32_t fb = bar + st * 8, dst = sb + st * STAGE;
        mbar_expect(fb, STAGE);
#pragma unroll
        for (int p = 0; p < 5; p++) tma5d(dst + 16384 + p * 8192, &mapB, half * 288 + p * 64, (kb0 + kb) * 2, fb);
        if (kb == NS - 1 || (kb == nkb - 1 && kb < NS - 1)) {
          asm volatile("griddepcontrol.wait;" ::: "memory");
          for (int k2 = 0; k2 <= kb; k2++) bulk_g2s(sb + k2 * STAGE, src + k2 * 1024, 16384, bar + k2 * 8);
        } else if (kb >= NS) bulk_g2s(dst, src + kb * 1024, 16384, fb);
        if (++st == NS) { st = 0; ph ^= 1; }
      }
    }
  } else {
    asm volatile("setmaxnreg.inc.sync.aligned.u32 232;");
    float a0[64], a1[80];
    int st = 0, ph = 0, prev = -1;
    for (int kb = 0; kb < nkb; kb++) {
      mbar_wait(bar + st * 8, ph, t0);
      const uint32_t aaddr = sb + st * STAGE + wg * 8192, baddr = sb + st * STAGE + 16384;
      wg_fence();
#pragma unroll
      for (int ks = 0; ks < 4; ks++) {
        const uint64_t da = make_desc(aaddr + ks * 256, 128, 1024, 0);
        wgmma_n128<0, 1>(a0, da, make_desc(baddr + ks * 2048, 8192, 1024, 1), (kb | ks) != 0);
        wgmma_n160<0, 1>(a1, da, make_desc(baddr + 16384 + ks * 2048, 8192, 1024, 1), (kb | ks) != 0);
      }
      wg_commit();
      if (prev >= 0) { wg_wait<1>(); if (lane == 0) mbar_arrive(bar + (NS + prev) * 8); }
      prev = st;
      if (++st == NS) { st = 0; ph ^= 1; }
    }
    wg_wait<0>();
    fence_regs(a0); fence_regs(a1);
    asm volatile("griddepcontrol.wait;" ::: "memory");
#pragma unroll
    for (int hi = 0; hi < 2; hi++) {
      uint4* dst = P + (((size_t)split * 256 + rb * 16 + wg * 8 + w * 2 + hi) * 18 + half * 9) * 32 + lane;
#pragma unroll
      for (int u = 0; u < 4; u++) {
        const float* c = &a0[u * 16 + hi * 2];
        stg128(dst + u * 32, pack2(c[0], c[1]), pack2(c[4], c[5]), pack2(c[8], c[9]), pack2(c[12], c[13]));
      }
#pragma unroll
      for (int u = 0; u < 5; u++) {
        const float* c = &a1[u * 16 + hi * 2];
        stg128(dst + (4 + u) * 32, pack2(c[0], c[1]), pack2(c[4], c[5]), pack2(c[8], c[9]), pack2(c[12], c[13]));
      }
    }
  }
}
}
typedef CUresult (*EncodeFn)(CUtensorMap*, CUtensorMapDataType, cuuint32_t, void*, const cuuint64_t*, const cuuint64_t*, const cuuint32_t*,
                             const cuuint32_t*, CUtensorMapInterleave, CUtensorMapSwizzle, CUtensorMapL2promotion, CUtensorMapFloatOOBfill);
static EncodeFn get_encode() {
  void* fn = nullptr; cudaDriverEntryPointQueryResult st;
  cudaGetDriverEntryPoint("cuTensorMapEncodeTiled", &fn, cudaEnableDefault, &st);
  return (EncodeFn)fn;
}
static CUtensorMap map2d(EncodeFn enc, const void* p, int rows, int cols, int brow) {
  CUtensorMap m;
  cuuint64_t dim[2] = {(cuuint64_t)cols, (cuuint64_t)rows}; cuuint64_t str[1] = {(cuuint64_t)cols * 2};
  cuuint32_t box[2] = {64, (cuuint32_t)brow}, es[2] = {1, 1};
  enc(&m, CU_TENSOR_MAP_DATA_TYPE_BFLOAT16, 2, (void*)p, dim, str, box, es, CU_TENSOR_MAP_INTERLEAVE_NONE, CU_TENSOR_MAP_SWIZZLE_128B,
      CU_TENSOR_MAP_L2_PROMOTION_L2_256B, CU_TENSOR_MAP_FLOAT_OOB_FILL_NONE);
  return m;
}
static CUtensorMap map5d(EncodeFn enc, const void* p, int rows, int cols) {
  CUtensorMap m;
  const cuuint64_t rs = (cuuint64_t)cols * 2;
  cuuint64_t dim[5] = {(cuuint64_t)cols, 2, 4, 4, (cuuint64_t)rows / 32}; cuuint64_t str[4] = {rs, 8 * rs, 2 * rs, 32 * rs};
  cuuint32_t box[5] = {64, 2, 4, 4, 2}, es[5] = {1, 1, 1, 1, 1};
  enc(&m, CU_TENSOR_MAP_DATA_TYPE_BFLOAT16, 5, (void*)p, dim, str, box, es, CU_TENSOR_MAP_INTERLEAVE_NONE, CU_TENSOR_MAP_SWIZZLE_128B,
      CU_TENSOR_MAP_L2_PROMOTION_L2_256B, CU_TENSOR_MAP_FLOAT_OOB_FILL_NONE);
  return m;
}
template <typename... KArgs, typename... Args>
static void launch(void (*k)(KArgs...), int grid, int block, int smem, cudaStream_t s, int cluster, bool pdl, Args... args) {
  cudaLaunchConfig_t cfg = {};
  cfg.gridDim = dim3(grid); cfg.blockDim = dim3(block); cfg.dynamicSmemBytes = smem; cfg.stream = s;
  cudaLaunchAttribute at[2]; int n = 0;
  if (cluster > 1) { at[n].id = cudaLaunchAttributeClusterDimension; at[n].val.clusterDim.x = cluster; at[n].val.clusterDim.y = 1; at[n].val.clusterDim.z = 1; n++; }
  if (pdl) { at[n].id = cudaLaunchAttributeProgrammaticStreamSerialization; at[n].val.programmaticStreamSerializationAllowed = 1; n++; }
  cfg.attrs = at; cfg.numAttrs = n;
  cudaLaunchKernelEx(&cfg, k, KArgs(args)...);
}
struct Ctx {
  CUtensorMap mWq, mWk, mWv, mWo5, mW15, mW25;
  uint4 *oT, *gT, *p1, *p2;
  cudaStream_t s2; cudaEvent_t evFork, evJoin;
  bool init;
};
static void setup(Ctx& c, void* const* d_in) {
  EncodeFn enc = get_encode();
  c.mWq = map2d(enc, d_in[2], DM, HD, 64); c.mWk = map2d(enc, d_in[3], DM, HD, 64); c.mWv = map2d(enc, d_in[4], DM, HD, 64);
  c.mWo5 = map5d(enc, d_in[5], HD, DM); c.mW15 = map5d(enc, d_in[8], DM, FF); c.mW25 = map5d(enc, d_in[10], FF, DM);
  cudaGetSymbolAddress((void**)&c.oT, g_oT); cudaGetSymbolAddress((void**)&c.gT, g_gT);
  cudaGetSymbolAddress((void**)&c.p1, g_p1); cudaGetSymbolAddress((void**)&c.p2, g_p2);
  cudaFuncSetAttribute(chain::chain_kernel, cudaFuncAttributeNonPortableClusterSizeAllowed, 1);
  cudaFuncSetAttribute(chain::chain_kernel, cudaFuncAttributeMaxDynamicSharedMemorySize, chain::SM_TOTAL);
  cudaFuncSetAttribute(bres::bres_kernel<0>, cudaFuncAttributeMaxDynamicSharedMemorySize, bres::SM_TOTAL);
  cudaFuncSetAttribute(bres::bres_kernel<1>, cudaFuncAttributeMaxDynamicSharedMemorySize, bres::SM_TOTAL);
  cudaFuncSetAttribute(bres::bres_kernel<2>, cudaFuncAttributeMaxDynamicSharedMemorySize, bres::SM_TOTAL);
  cudaFuncSetAttribute(sk::sk_kernel, cudaFuncAttributeMaxDynamicSharedMemorySize, sk::SM_TOTAL);
  cudaFuncAttributes fa;
  cudaFuncGetAttributes(&fa, ln1_kernel); cudaFuncGetAttributes(&fa, ln2_kernel<4>); cudaFuncGetAttributes(&fa, fin_kernel<4>);
  int lo, hi; cudaDeviceGetStreamPriorityRange(&lo, &hi);
  cudaStreamCreateWithPriority(&c.s2, cudaStreamNonBlocking, hi);
  cudaEventCreateWithFlags(&c.evFork, cudaEventDisableTiming); cudaEventCreateWithFlags(&c.evJoin, cudaEventDisableTiming);
  c.init = true;
}
static Ctx g_ctx;
extern "C" void kernel_launch(void* const* d_in, const int* in_sizes, int n_in, void* d_out, int out_size) {
  Ctx& c = g_ctx;
  if (!c.init) setup(c, d_in);
  const bf16 *x = (const bf16*)d_in[0], *mem0 = (const bf16*)d_in[1], *Wq = (const bf16*)d_in[2], *Wk = (const bf16*)d_in[3],
             *Wv = (const bf16*)d_in[4], *Wo = (const bf16*)d_in[5], *b1 = (const bf16*)d_in[9], *b2 = (const bf16*)d_in[11];
  bf16* out = (bf16*)d_out;
  cudaStream_t s = cudaStreamPerThread;
  cudaEventRecord(c.evFork, s);
  cudaStreamWaitEvent(c.s2, c.evFork, 0);
  launch(chain::chain_kernel, 64, chain::NTHREADS, chain::SM_TOTAL, c.s2, 16, false, mem0, Wq, Wk, Wv, Wo, 0u);
  cudaEventRecord(c.evJoin, c.s2);
  launch(ln1_kernel, 256, 192, 0, s, 1, false, x);
  launch(bres::bres_kernel<0>, 64, 384, bres::SM_TOTAL, s, 1, true, c.mWk, c.mWv, (const bf16*)0, 64, 0, 1, 16);
  launch(bres::bres_kernel<1>, 64, 384, bres::SM_TOTAL, s, 1, true, c.mWq, c.mWq, (const bf16*)0, 32, 0, 2, 8);
  launch(sk::sk_kernel, 128, 384, sk::SM_TOTAL, s, 1, true, c.mWo5, c.oT, c.p1, 64, 4, 0);
  launch(ln2_kernel<4>, 256, 192, 0, s, 1, true, x, 0);
  launch(bres::bres_kernel<2>, 108, 384, bres::SM_TOTAL, s, 1, true, c.mW15, c.mW15, b1, 36, 0, 3, -1);
  launch(sk::sk_kernel, 128, 384, sk::SM_TOTAL, s, 1, true, c.mW25, c.gT, c.p2, 72, 4, 0);
  launch(fin_kernel<4>, 256, 192, 0, s, 1, true, b2, out, 0, 1);
  cudaStreamWaitEvent(s, c.evJoin, 0);
}
```

```cpp
#include <cuda_runtime.h>
#include <cuda_bf16.h>
#include <cuda.h>
#include <stdint.h>

typedef __nv_bfloat16 bf16;

constexpr int SEQ = 2048, DM = 576, NH = 32, DH = 128, HD = 4096, FF = 4608, NSEG = 64, NRB = 16;

__device__ __align__(1024) uint4 g_Kf[NH * 256 * 4 * 32];
__device__ __align__(1024) uint4 g_Vf[NH * NSEG * 128 * 4];
__device__ __align__(1024) uint4 g_Kmf[NH * NSEG * 4 * 32];
__device__ __align__(1024) uint4 g_Vmf[NH * NSEG * 4 * 32];
__device__ __align__(8192) uint4 g_xch[64 * 512];
__device__ unsigned g_kvflag[NRB * 64];
__device__ unsigned g_memflag[NH * 8];
__device__ __align__(1024) uint4 g_xnT[NRB * 9 * 1024];
__device__ unsigned g_cntX[NRB * 32];
__device__ unsigned g_epoch;
__device__ unsigned g_resident;
__device__ unsigned g_err;

__device__ __forceinline__ uint32_t smem_u32(const void* p) { return (uint32_t)__cvta_generic_to_shared(p); }
__device__ __forceinline__ void mbar_init(uint32_t a, int cnt) { asm volatile("mbarrier.init.shared::cta.b64 [%0], %1;" :: "r"(a), "r"(cnt) : "memory"); }
__device__ __forceinline__ void mbar_expect(uint32_t a, int bytes) { asm volatile("mbarrier.arrive.expect_tx.shared::cta.b64 _, [%0], %1;" :: "r"(a), "r"(bytes) : "memory"); }
__device__ __forceinline__ void mbar_arrive(uint32_t a) { asm volatile("mbarrier.arrive.shared::cta.b64 _, [%0];" :: "r"(a) : "memory"); }
__device__ __forceinline__ void mbar_arrive_if(uint32_t a, int p) { asm volatile("{ .reg .pred q; setp.ne.b32 q, %1, 0; @q mbarrier.arrive.shared::cta.b64 _, [%0]; }" :: "r"(a), "r"(p) : "memory"); }
__device__ __forceinline__ bool mbar_try(uint32_t a, uint32_t parity) {
  uint32_t ok;
  asm volatile("{ .reg .pred p; mbarrier.try_wait.parity.shared::cta.b64 p, [%1], %2; selp.u32 %0, 1, 0, p; }" : "=r"(ok) : "r"(a), "r"(parity) : "memory");
  return ok;
}
__device__ __forceinline__ bool mbar_test(uint32_t a, uint32_t parity) {
  uint32_t ok;
  asm volatile("{ .reg .pred p; mbarrier.test_wait.parity.shared::cta.b64 p, [%1], %2; selp.u32 %0, 1, 0, p; }" : "=r"(ok) : "r"(a), "r"(parity) : "memory");
  return ok;
}
__device__ __forceinline__ bool mbar_try_cl(uint32_t a, uint32_t parity) {
  uint32_t ok;
  asm volatile("{ .reg .pred p; mbarrier.try_wait.parity.acquire.cluster.shared::cta.b64 p, [%1], %2; selp.u32 %0, 1, 0, p; }" : "=r"(ok) : "r"(a), "r"(parity) : "memory");
  return ok;
}
__device__ __forceinline__ uint32_t clk32() { uint32_t c; asm volatile("mov.u32 %0, %%clock;" : "=r"(c)); return c; }
constexpr uint32_t TIMEOUT_CLKS = 400000000u;
__device__ __forceinline__ bool timed_out(uint32_t t0) {
  if (clk32() - t0 > TIMEOUT_CLKS) { g_err = 1; return true; }
  return false;
}
__device__ __forceinline__ void mbar_wait(uint32_t a, uint32_t parity, uint32_t t0) {
  while (!mbar_try(a, parity)) { if (timed_out(t0)) break; }
}
__device__ __forceinline__ void mbar_wait_cl(uint32_t a, uint32_t parity, uint32_t t0) {
  while (!mbar_try_cl(a, parity)) { if (timed_out(t0)) break; }
}
__device__ __forceinline__ uint32_t mapa(uint32_t a, uint32_t r) { uint32_t d; asm volatile("mapa.shared::cluster.u32 %0, %1, %2;" : "=r"(d) : "r"(a), "r"(r)); return d; }
__device__ __forceinline__ void st_async16(uint32_t a, uint32_t x, uint32_t y, uint32_t z, uint32_t w, uint32_t bar) {
  asm volatile("st.async.shared::cluster.mbarrier::complete_tx::bytes.v4.b32 [%0], {%1,%2,%3,%4}, [%5];" :: "r"(a), "r"(x), "r"(y), "r"(z), "r"(w), "r"(bar) : "memory");
}
__device__ __forceinline__ void st_async8(uint32_t a, uint32_t x, uint32_t y, uint32_t bar) {
  asm volatile("st.async.shared::cluster.mbarrier::complete_tx::bytes.v2.b32 [%0], {%1,%2}, [%3];" :: "r"(a), "r"(x), "r"(y), "r"(bar) : "memory");
}
__device__ __forceinline__ void bar_sync(int id, int n) { asm volatile("bar.sync %0, %1;" :: "r"(id), "r"(n) : "memory"); }
__device__ __forceinline__ void bar_arrive(int id, int n) { asm volatile("bar.arrive %0, %1;" :: "r"(id), "r"(n) : "memory"); }
__device__ __forceinline__ void cluster_sync() { asm volatile("barrier.cluster.arrive.release.aligned; barrier.cluster.wait.acquire.aligned;" ::: "memory"); }
__device__ __forceinline__ uint32_t pack2(float lo, float hi) { uint32_t d; asm("cvt.rn.bf16x2.f32 %0, %1, %2;" : "=r"(d) : "f"(hi), "f"(lo)); return d; }
__device__ __forceinline__ float bflo(uint32_t v) { return __uint_as_float(v << 16); }
__device__ __forceinline__ float bfhi(uint32_t v) { return __uint_as_float(v & 0xffff0000u); }
__device__ __forceinline__ uint32_t movmat(uint32_t a) { uint32_t d; asm volatile("movmatrix.sync.aligned.m8n8.trans.b16 %0, %1;" : "=r"(d) : "r"(a)); return d; }
__device__ __forceinline__ uint32_t hadd2bf(uint32_t a, uint32_t b) { uint32_t d; asm("add.rn.bf16x2 %0, %1, %2;" : "=r"(d) : "r"(a), "r"(b)); return d; }
__device__ __forceinline__ void mma16816(float (&c)[4], uint32_t a0, uint32_t a1, uint32_t a2, uint32_t a3, uint32_t b0, uint32_t b1) {
  asm volatile("mma.sync.aligned.m16n8k16.row.col.f32.bf16.bf16.f32 {%0,%1,%2,%3}, {%4,%5,%6,%7}, {%8,%9}, {%0,%1,%2,%3};"
    : "+f"(c[0]), "+f"(c[1]), "+f"(c[2]), "+f"(c[3]) : "r"(a0), "r"(a1), "r"(a2), "r"(a3), "r"(b0), "r"(b1));
}
__device__ __forceinline__ void mma16816(float (&c)[4], const uint32_t (&a)[4], uint32_t b0, uint32_t b1) { mma16816(c, a[0], a[1], a[2], a[3], b0, b1); }
__device__ __forceinline__ void mma1688(float (&c)[4], uint32_t a0, uint32_t a1, uint32_t b0) {
  asm volatile("mma.sync.aligned.m16n8k8.row.col.f32.bf16.bf16.f32 {%0,%1,%2,%3}, {%4,%5}, {%6}, {%0,%1,%2,%3};"
    : "+f"(c[0]), "+f"(c[1]), "+f"(c[2]), "+f"(c[3]) : "r"(a0), "r"(a1), "r"(b0));
}
__device__ __forceinline__ void ldsm4t(uint32_t (&r)[4], uint32_t a) {
  asm volatile("ldmatrix.sync.aligned.m8n8.x4.trans.shared.b16 {%0,%1,%2,%3}, [%4];" : "=r"(r[0]), "=r"(r[1]), "=r"(r[2]), "=r"(r[3]) : "r"(a) : "memory");
}
__device__ __forceinline__ uint4 lds128(uint32_t a) { uint4 v; asm volatile("ld.shared.v4.b32 {%0,%1,%2,%3}, [%4];" : "=r"(v.x), "=r"(v.y), "=r"(v.z), "=r"(v.w) : "r"(a) : "memory"); return v; }
__device__ __forceinline__ uint2 lds64(uint32_t a) { uint2 v; asm volatile("ld.shared.v2.b32 {%0,%1}, [%2];" : "=r"(v.x), "=r"(v.y) : "r"(a) : "memory"); return v; }
__device__ __forceinline__ void sts128(uint32_t a, uint32_t x, uint32_t y, uint32_t z, uint32_t w) { asm volatile("st.shared.v4.b32 [%0], {%1,%2,%3,%4};" :: "r"(a), "r"(x), "r"(y), "r"(z), "r"(w) : "memory"); }
__device__ __forceinline__ void sts64(uint32_t a, uint32_t x, uint32_t y) { asm volatile("st.shared.v2.b32 [%0], {%1,%2};" :: "r"(a), "r"(x), "r"(y) : "memory"); }
__device__ __forceinline__ void sts32(uint32_t a, uint32_t x) { asm volatile("st.shared.b32 [%0], %1;" :: "r"(a), "r"(x) : "memory"); }
__device__ __forceinline__ void cp_async16(uint32_t dst, const void* src) { asm volatile("cp.async.cg.shared.global [%0], [%1], 16;" :: "r"(dst), "l"(src) : "memory"); }
__device__ __forceinline__ void cp_async_wait_all() { asm volatile("cp.async.wait_all;" ::: "memory"); }
__device__ __forceinline__ uint4 ldg_cg(const void* p) { uint4 v; asm volatile("ld.global.cg.v4.b32 {%0,%1,%2,%3}, [%4];" : "=r"(v.x), "=r"(v.y), "=r"(v.z), "=r"(v.w) : "l"(p) : "memory"); return v; }
__device__ __forceinline__ uint4 ld_relaxed16(const void* p) { uint4 v; asm volatile("ld.relaxed.gpu.global.v4.b32 {%0,%1,%2,%3}, [%4];" : "=r"(v.x), "=r"(v.y), "=r"(v.z), "=r"(v.w) : "l"(p) : "memory"); return v; }
__device__ __forceinline__ void st_relaxed16(void* p, uint32_t x, uint32_t y, uint32_t z, uint32_t w) { asm volatile("st.relaxed.gpu.global.v4.b32 [%0], {%1,%2,%3,%4};" :: "l"(p), "r"(x), "r"(y), "r"(z), "r"(w) : "memory"); }
__device__ __forceinline__ unsigned ld_acquire(const unsigned* p) { unsigned v; asm volatile("ld.acquire.gpu.global.u32 %0, [%1];" : "=r"(v) : "l"(p) : "memory"); return v; }
__device__ __forceinline__ uint32_t ldg32(const void* p) { uint32_t v; asm volatile("ld.global.nc.b32 %0, [%1];" : "=r"(v) : "l"(p)); return v; }
__device__ __forceinline__ unsigned ld_relaxed(const unsigned* p) { unsigned v; asm volatile("ld.relaxed.gpu.global.u32 %0, [%1];" : "=r"(v) : "l"(p) : "memory"); return v; }
__device__ __forceinline__ void st_release(unsigned* p, unsigned v) { asm volatile("st.release.gpu.global.u32 [%0], %1;" :: "l"(p), "r"(v) : "memory"); }
__device__ __forceinline__ float ex2(float x) { float y; asm("ex2.approx.ftz.f32 %0, %1;" : "=f"(y) : "f"(x)); return y; }

__device__ __forceinline__ void st_b128(void* p, uint32_t x, uint32_t y, uint32_t z, uint32_t w) {
  asm volatile("{ .reg .b128 t; .reg .b64 lo, hi; mov.b64 lo, {%1,%2}; mov.b64 hi, {%3,%4}; mov.b128 t, {lo,hi}; st.relaxed.gpu.global.b128 [%0], t; }"
    :: "l"(p), "r"(x), "r"(y), "r"(z), "r"(w) : "memory");
}
__device__ __forceinline__ uint4 ld_b128(const void* p) {
  uint4 v;
  asm volatile("{ .reg .b128 t; .reg .b64 lo, hi; ld.relaxed.gpu.global.b128 t, [%4]; mov.b128 {lo,hi}, t; mov.b64 {%0,%1}, lo; mov.b64 {%2,%3}, hi; }"
    : "=r"(v.x), "=r"(v.y), "=r"(v.z), "=r"(v.w) : "l"(p) : "memory");
  return v;
}
__device__ __forceinline__ void wg_fence() { asm volatile("wgmma.fence.sync.aligned;" ::: "memory"); }
__device__ __forceinline__ void wg_commit() { asm volatile("wgmma.commit_group.sync.aligned;" ::: "memory"); }
template <int N> __device__ __forceinline__ void wg_wait() { asm volatile("wgmma.wait_group.sync.aligned %0;" :: "n"(N) : "memory"); }
__device__ __forceinline__ uint64_t make_desc(uint32_t addr, uint32_t lbo, uint32_t sbo, uint32_t mode) {
  return (uint64_t)((addr & 0x3FFFF) >> 4) | ((uint64_t)(lbo >> 4) << 16) | ((uint64_t)(sbo >> 4) << 32) | ((uint64_t)mode << 62);
}
__device__ __forceinline__ void tma2d(uint32_t dst, const CUtensorMap* m, int c0, int c1, uint32_t bar) {
  asm volatile("cp.async.bulk.tensor.2d.shared::cluster.global.mbarrier::complete_tx::bytes [%0], [%1, {%3, %4}], [%2];"
    :: "r"(dst), "l"(m), "r"(bar), "r"(c0), "r"(c1) : "memory");
}
__device__ __forceinline__ void tma5d(uint32_t dst, const CUtensorMap* m, int c0, int c4, uint32_t bar) {
  asm volatile("cp.async.bulk.tensor.5d.shared::cluster.global.mbarrier::complete_tx::bytes [%0], [%1, {%3, %5, %5, %5, %4}], [%2];"
    :: "r"(dst), "l"(m), "r"(bar), "r"(c0), "r"(c4), "r"(0) : "memory");
}
__device__ __forceinline__ void bulk_g2s(uint32_t dst, const void* src, uint32_t bytes, uint32_t bar) {
  asm volatile("cp.async.bulk.shared::cluster.global.mbarrier::complete_tx::bytes [%0], [%1], %2, [%3];" :: "r"(dst), "l"(src), "r"(bytes), "r"(bar) : "memory");
}
__device__ __forceinline__ void stg128(void* p, uint32_t x, uint32_t y, uint32_t z, uint32_t w) {
  asm volatile("st.global.v4.b32 [%0], {%1,%2,%3,%4};" :: "l"(p), "r"(x), "r"(y), "r"(z), "r"(w) : "memory");
}
template <int N> __device__ __forceinline__ void fence_regs(float (&d)[N]) {
#pragma unroll
  for (int i = 0; i < N; i++) asm volatile("" : "+f"(d[i]) :: "memory");
}

#define TR_T(v)
#define TR_VAR(v)
#define TR_SET(v)
#define TR_LOG(info, a, b)
template <int TA, int TB>
__device__ __forceinline__ void wgmma_n96(float (&d)[64], uint64_t da, uint64_t db, int scale_d) {
  asm volatile("{ .reg .pred p; setp.ne.b32 p, %50, 0;\n"
    "wgmma.mma_async.sync.aligned.m64n96k16.f32.bf16.bf16 {%0, %1, %2, %3, %4, %5, %6, %7, %8, %9, %10, %11, %12, %13, %14, %15, %16, %17, %18, %19, %20, %21, %22, %23, %24, %25, %26, %27, %28, %29, %30, %31, %32, %33, %34, %35, %36, %37, %38, %39, %40, %41, %42, %43, %44, %45, %46, %47}, %48, %49, p, 1, 1, %51, %52; }"
    : "+f"(d[0]), "+f"(d[1]), "+f"(d[2]), "+f"(d[3]), "+f"(d[4]), "+f"(d[5]), "+f"(d[6]), "+f"(d[7]), "+f"(d[8]), "+f"(d[9]), "+f"(d[10]), "+f"(d[11]), "+f"(d[12]), "+f"(d[13]), "+f"(d[14]), "+f"(d[15]), "+f"(d[16]), "+f"(d[17]), "+f"(d[18]), "+f"(d[19]), "+f"(d[20]), "+f"(d[21]), "+f"(d[22]), "+f"(d[23]), "+f"(d[24]), "+f"(d[25]), "+f"(d[26]), "+f"(d[27]), "+f"(d[28]), "+f"(d[29]), "+f"(d[30]), "+f"(d[31]), "+f"(d[32]), "+f"(d[33]), "+f"(d[34]), "+f"(d[35]), "+f"(d[36]), "+f"(d[37]), "+f"(d[38]), "+f"(d[39]), "+f"(d[40]), "+f"(d[41]), "+f"(d[42]), "+f"(d[43]), "+f"(d[44]), "+f"(d[45]), "+f"(d[46]), "+f"(d[47])
    : "l"(da), "l"(db), "r"(scale_d), "n"(TA), "n"(TB));
}
template <int TA, int TB>
__device__ __forceinline__ void wgmma_n128(float (&d)[64], uint64_t da, uint64_t db, int scale_d) {
  asm volatile("{ .reg .pred p; setp.ne.b32 p, %66, 0;\n"
    "wgmma.mma_async.sync.aligned.m64n128k16.f32.bf16.bf16 {%0, %1, %2, %3, %4, %5, %6, %7, %8, %9, %10, %11, %12, %13, %14, %15, %16, %17, %18, %19, %20, %21, %22, %23, %24, %25, %26, %27, %28, %29, %30, %31, %32, %33, %34, %35, %36, %37, %38, %39, %40, %41, %42, %43, %44, %45, %46, %47, %48, %49, %50, %51, %52, %53, %54, %55, %56, %57, %58, %59, %60, %61, %62, %63}, %64, %65, p, 1, 1, %67, %68; }"
    : "+f"(d[0]), "+f"(d[1]), "+f"(d[2]), "+f"(d[3]), "+f"(d[4]), "+f"(d[5]), "+f"(d[6]), "+f"(d[7]), "+f"(d[8]), "+f"(d[9]), "+f"(d[10]), "+f"(d[11]), "+f"(d[12]), "+f"(d[13]), "+f"(d[14]), "+f"(d[15]), "+f"(d[16]), "+f"(d[17]), "+f"(d[18]), "+f"(d[19]), "+f"(d[20]), "+f"(d[21]), "+f"(d[22]), "+f"(d[23]), "+f"(d[24]), "+f"(d[25]), "+f"(d[26]), "+f"(d[27]), "+f"(d[28]), "+f"(d[29]), "+f"(d[30]), "+f"(d[31]), "+f"(d[32]), "+f"(d[33]), "+f"(d[34]), "+f"(d[35]), "+f"(d[36]), "+f"(d[37]), "+f"(d[38]), "+f"(d[39]), "+f"(d[40]), "+f"(d[41]), "+f"(d[42]), "+f"(d[43]), "+f"(d[44]), "+f"(d[45]), "+f"(d[46]), "+f"(d[47]), "+f"(d[48]), "+f"(d[49]), "+f"(d[50]), "+f"(d[51]), "+f"(d[52]), "+f"(d[53]), "+f"(d[54]), "+f"(d[55]), "+f"(d[56]), "+f"(d[57]), "+f"(d[58]), "+f"(d[59]), "+f"(d[60]), "+f"(d[61]), "+f"(d[62]), "+f"(d[63])
    : "l"(da), "l"(db), "r"(scale_d), "n"(TA), "n"(TB));
}
#define POLL_MODE 1
#define STAGGER 0
#define WEARLY 6
#define WLATE 1
#define PREF 1
#define POLL_REP 2
namespace chain {
constexpr int SLOT = 4096;
constexpr int NX = 8;
constexpr int NPV = 9;
constexpr int NV2 = 18 - NPV;
constexpr int NPERM = 2 * (18 - NX) + NPV;
constexpr int SM_X = 0;
constexpr int SM_V2 = SM_X + 2 * NX * SLOT;
constexpr int SM_KX = SM_V2 + NV2 * SLOT;
constexpr int SM_VX = SM_KX + 8192;
constexpr int SM_WO = SM_VX + 8192;
static_assert(SM_WO == NPERM * SLOT, "staging area = X + V2 + KX + VX");
constexpr int SM_MEM = SM_WO + 5 * 16384;
constexpr int SM_OQK = SM_MEM + 9 * 512;
constexpr int SM_XQK = SM_OQK + 4096;
constexpr int SM_OV = SM_XQK + 4096;
constexpr int SM_XV = SM_OV + 2048;
constexpr int SM_S = SM_XV + 2048;
constexpr int SM_O = SM_S + 1536;
constexpr int SM_RS = SM_O + 2048;
constexpr int SM_MB = SM_RS + 8 * 576;
constexpr int SM_INV = SM_MB + 3 * 1152;
constexpr int SM_BAR = SM_INV + 128;
constexpr int SM_PROF = SM_BAR + 128;
constexpr int SM_TOTAL = SM_PROF + 256;
static_assert(SM_TOTAL <= 232448, "smem");
constexpr int B_AG = 0  , B_XQK = 40, B_XV = 48, B_RS = 56, B_KV = 64, B_L = 72, B_W = 80  ;
constexpr int RS_BYTES = 7 * 512 + 8 * 64;
constexpr int BAR_OQK = 1, BAR_S = 2, BAR_O = 3, BAR_ALL = 4, BAR_L = 5, BAR_AB = 6, BAR_AB2 = 7, BAR_C = 8;
constexpr int NTHREADS = 384;
constexpr int REG_C = 216, REG_A = 72;
static_assert(2 * REG_C + REG_A <= 504, "register pool");

#define PROF(slot) do {} while (0)
#define PROFN(slot) do {} while (0)
#define PROFS() do {} while (0)
#define PROF0(slot) do {} while (0)
#define PROF1(slot) do {} while (0)

struct Maps { CUtensorMap q, k, v, o; };
__device__ int g_side[133];
__device__ unsigned g_elect;

__device__ __forceinline__ void mmaq(float (&c)[4], const uint4& a, uint32_t b0, uint32_t b1) { mma16816(c, a.x, a.y, a.z, a.w, b0, b1); }
__device__ __forceinline__ int opaque(int v) { int d; asm volatile("mov.u32 %0, %1;" : "=r"(d) : "r"(v)); return d; }
__device__ __forceinline__ uint32_t dep(uint32_t base, uint32_t v, uint32_t zero) {
  uint32_t d; asm("lop3.b32 %0, %1, %2, %3, 0xF8;" : "=r"(d) : "r"(base), "r"(v), "r"(zero)); return d;
}
__device__ __forceinline__ void tma3d(uint32_t dst, const CUtensorMap* m, int c1, int c2, uint32_t bar) {
  asm volatile("cp.async.bulk.tensor.3d.shared::cluster.global.mbarrier::complete_tx::bytes [%0], [%1, {%5, %3, %4}], [%2];"
    :: "r"(dst), "l"(m), "r"(bar), "r"(c1), "r"(c2), "r"(0) : "memory");
}
__device__ __forceinline__ void tma3d_prefetch(const CUtensorMap* m, int c1, int c2) {
  asm volatile("cp.async.bulk.prefetch.tensor.3d.L2.global [%0, {%3, %1, %2}];" :: "l"(m), "r"(c1), "r"(c2), "r"(0) : "memory");
}
__device__ __forceinline__ uint32_t frag_off(int lane, int cp) {
  const int mat = lane >> 3, r = lane & 7;
  return ((mat >> 1) * 8 + r) * 128 + (((cp * 2 + (mat & 1)) ^ r) * 16);
}

template <bool EXTRA>
__device__ __forceinline__ void softmax_pv(int s, int x, uint32_t sb, uint32_t sl, uint32_t bar, int lane_in, int a, int head, uint32_t t0,
                                           uint32_t (&WX)[8][4], int P) {
  const int lane = opaque(lane_in);
  uint4* const vm_ptr = g_Vmf + (size_t)head * NSEG * 128 + x * 32 + lane;
  const float sc = 0.08838834764831845f * 1.4426950408889634f;
  uint4 vx[4];
#pragma unroll
  for (int u = 0; u < 4; u++) vx[u] = lds128(sl + SM_VX + x * 2048 + u * 512);
  bar_sync(BAR_S, 128);
  const uint4 s0 = lds128(sl + SM_S), s1 = lds128(sl + SM_S + 512), s2 = lds128(sl + SM_S + 1024);
  const bool okv = mbar_try(bar + B_XV, s & 1);
  const uint32_t lv = sb + x * 512 + lane * 8;
  float y[10] = {__uint_as_float(s0.x), __uint_as_float(s0.y), __uint_as_float(s0.z), __uint_as_float(s0.w),
                 __uint_as_float(s1.x), __uint_as_float(s1.y), __uint_as_float(s1.z), __uint_as_float(s1.w),
                 __uint_as_float(s2.x) + __uint_as_float(s2.z), __uint_as_float(s2.y) + __uint_as_float(s2.w)};
  float m = fmaxf(fmaxf(fmaxf(y[0], y[1]), fmaxf(y[2], y[3])), fmaxf(fmaxf(y[4], y[5]), fmaxf(y[6], y[7])));
  m = fmaxf(m, fmaxf(y[8], y[9]));
  if (P) PROF(12);
  m = fmaxf(m, __shfl_xor_sync(0xffffffffu, m, 1));
  m = fmaxf(m, __shfl_xor_sync(0xffffffffu, m, 2));
  if (!okv) mbar_wait(bar + B_XV, s & 1, t0);
  const uint2 ov0 = lds64(lv + SM_OV), xv0 = lds64(lv + SM_XV), ov1 = lds64(lv + SM_OV + 256), xv1 = lds64(lv + SM_XV + 256);
  const float mc = m * sc;
#pragma unroll
  for (int i = 0; i < 10; i++) y[i] = ex2(fmaf(y[i], sc, -mc));
  const uint32_t p0 = pack2(y[0], y[1]), p1 = pack2(y[2], y[3]), p2 = pack2(y[4], y[5]), p3 = pack2(y[6], y[7]), p4 = pack2(y[8], y[9]);
  const uint4 vm = make_uint4(hadd2bf(ov0.x, xv0.x), hadd2bf(ov0.y, xv0.y), hadd2bf(ov1.x, xv1.x), hadd2bf(ov1.y, xv1.y));
  float o0[4] = {0.f, 0.f, 0.f, 0.f}, o1[4] = {0.f, 0.f, 0.f, 0.f}, o2[4] = {0.f, 0.f, 0.f, 0.f}, o3[4] = {0.f, 0.f, 0.f, 0.f};
  mmaq(o0, vx[0], p0, p1); mmaq(o2, vx[2], p0, p1);
  mmaq(o0, vx[1], p2, p3); mmaq(o2, vx[3], p2, p3);
  mma1688(o1, vm.x, vm.y, p4); mma1688(o3, vm.z, vm.w, p4);
  asm volatile("stmatrix.sync.aligned.m8n8.x4.shared.b16 [%0], {%1,%2,%3,%4};" :: "r"(sl + SM_O + x * 512),
    "r"(pack2(o0[0] + o1[0], o0[1] + o1[1])), "r"(pack2(o0[2] + o1[2], o0[3] + o1[3])),
    "r"(pack2(o2[0] + o3[0], o2[1] + o3[1])), "r"(pack2(o2[2] + o3[2], o2[3] + o3[3])) : "memory");
  if (P) PROF(13);
  bar_arrive(BAR_O, NTHREADS);
  if (EXTRA) {
    const uint32_t wa = sb + SM_WO + 4 * 16384 + frag_off(lane, x);
#pragma unroll
    for (int u = 0; u < 8; u++) ldsm4t(WX[u], wa + u * 2048);
    bar_sync(BAR_AB2, 128);
  } else {
    bar_arrive(BAR_AB2, 128);
    if (x == 3) {
      float l = ((y[0] + y[1]) + (y[2] + y[3])) + ((y[4] + y[5]) + (y[6] + y[7])) + (y[8] + y[9]);
      l += __shfl_xor_sync(0xffffffffu, l, 1);
      l += __shfl_xor_sync(0xffffffffu, l, 2);
      float inv; asm("rcp.approx.ftz.f32 %0, %1;" : "=f"(inv) : "f"(l));
      if ((lane & 3) == 0) sts32(sb + SM_INV + lane, __float_as_uint(inv));
      __syncwarp();
      mbar_arrive_if(bar + B_L, lane == 0 && s >= 0);
    }
  }
  if (a == 0 && s >= 0) vm_ptr[(size_t)s * 128] = vm;
}

__device__ __forceinline__ void reduce_exchange(int x, int gi, int a, int s, uint32_t sb, uint32_t bar, int lane_in, uint32_t t0, int P, int bid) {
  const int lane = opaque(lane_in);
  const int tt = x * 32 + lane;
  const bool act = tt < 72;
  const int hc = lane & 1;
  const uint32_t rs_addr = sb + SM_RS + tt * 8;
  const uint32_t mem_addr = sb + SM_MEM + (x < 2 ? (tt >> 1) * 16 : 8 * 512 + (4 * gi + (lane >> 1)) * 16);
  const uint32_t mem_step = x < 2 ? 512 : 0;
  const uint32_t ma = mem_addr + (1 + hc) * mem_step;
  const uint32_t r0 = 2 * ((gi - 1 - hc) & 7) + a, r1 = 2 * ((gi - 3 - hc) & 7) + a, r2 = 2 * ((gi - 5 - hc) & 7) + a, r3 = 2 * ((gi - 7) & 7) + a;
  const uint32_t d0 = mapa(ma, r0), e0 = mapa(bar + B_AG + (x < 2 ? 8 : 32), r0);
  const uint32_t d1 = mapa(ma + 2 * mem_step, r1), e1_ = mapa(bar + B_AG + (x < 2 ? 16 : 32), r1);
  const uint32_t d2 = mapa(ma + 4 * mem_step, r2), e2_ = mapa(bar + B_AG + (x < 2 ? 24 : 32), r2);
  const uint32_t d3 = mapa(ma + 6 * mem_step, r3), e3_ = mapa(bar + B_AG + 32, r3);
  char* const xb = reinterpret_cast<char*>(g_xch) + (tt * 16 + (s & 1) * 2048);
  void* const xw = xb + (size_t)bid * 8192;
  const void* const xr1 = xb + (size_t)(bid ^ 16) * 8192;
  const void* const xr2 = xb + (size_t)(bid ^ 32) * 8192;
  const void* const xr3 = xb + (size_t)(bid ^ 48) * 8192;
  const uint32_t tag = (s + 1) & 15;
  mbar_wait(bar + B_RS, s & 1, t0);
  if (P) PROF(20);
  uint32_t w0 = 0, w1 = 0;
  if (act) {
    uint2 r[8];
#pragma unroll
    for (int u = 0; u < 8; u++) r[u] = lds64(rs_addr + u * 576);
    float f0 = ((bflo(r[0].x) + bflo(r[1].x)) + (bflo(r[2].x) + bflo(r[3].x))) + ((bflo(r[4].x) + bflo(r[5].x)) + (bflo(r[6].x) + bflo(r[7].x)));
    float f1 = ((bfhi(r[0].x) + bfhi(r[1].x)) + (bfhi(r[2].x) + bfhi(r[3].x))) + ((bfhi(r[4].x) + bfhi(r[5].x)) + (bfhi(r[6].x) + bfhi(r[7].x)));
    float f2 = ((bflo(r[0].y) + bflo(r[1].y)) + (bflo(r[2].y) + bflo(r[3].y))) + ((bflo(r[4].y) + bflo(r[5].y)) + (bflo(r[6].y) + bflo(r[7].y)));
    float f3 = ((bfhi(r[0].y) + bfhi(r[1].y)) + (bfhi(r[2].y) + bfhi(r[3].y))) + ((bfhi(r[4].y) + bfhi(r[5].y)) + (bfhi(r[6].y) + bfhi(r[7].y)));
    const uint32_t m0 = (__float_as_uint(f0) & ~15u) | tag;
    if (s >= 0) st_b128(xw, m0, __float_as_uint(f1), __float_as_uint(f2), __float_as_uint(f3));
    if (P) PROF(21);
    uint4 e1, e2, e3;
    const uint32_t mb = sb + SM_MB + tt * 16;
    while (true) {
      cp_async16(mb, xr1); cp_async16(mb + 1152, xr2); cp_async16(mb + 2304, xr3);
      bool ok = false;
#pragma unroll
      for (int i = 0; i < POLL_REP; i++) {
        e1 = lds128(mb); e2 = lds128(mb + 1152); e3 = lds128(mb + 2304);
        ok = (((e1.x ^ tag) | (e2.x ^ tag) | (e3.x ^ tag)) & 15u) == 0;
        if (ok) break;
      }
      if (ok || s < 0 || timed_out(t0)) break;
    }
    if (P) PROF(22);
    f0 = (__uint_as_float(m0) + __uint_as_float(e1.x)) + (__uint_as_float(e2.x) + __uint_as_float(e3.x));
    f1 = (f1 + __uint_as_float(e1.y)) + (__uint_as_float(e2.y) + __uint_as_float(e3.y));
    f2 = (f2 + __uint_as_float(e1.z)) + (__uint_as_float(e2.z) + __uint_as_float(e3.z));
    f3 = (f3 + __uint_as_float(e1.w)) + (__uint_as_float(e2.w) + __uint_as_float(e3.w));
    w0 = pack2(f0, f1); w1 = pack2(f2, f3);
    if (s >= 0) sts64(mem_addr + hc * 8, w0, w1);
  }
  __syncwarp();
  const uint32_t n0 = __shfl_xor_sync(0xffffffffu, w0, 1), n1 = __shfl_xor_sync(0xffffffffu, w1, 1);
  mbar_arrive_if(bar + B_AG + (x == 2 ? 32 : 0), lane == 0);
  if (act && s >= 0) {
    const uint32_t y0 = hc ? n0 : w0, y1 = hc ? n1 : w1, y2 = hc ? w0 : n0, y3 = hc ? w1 : n1;
    st_async16(d0, y0, y1, y2, y3, e0);
    st_async16(d1, y0, y1, y2, y3, e1_);
    st_async16(d2, y0, y1, y2, y3, e2_);
    if (!hc) st_async16(d3, y0, y1, y2, y3, e3_);
  }
  __syncwarp();
  if (P) PROF(23);
}

__global__ void __launch_bounds__(NTHREADS, 1)
chain_kernel(const __grid_constant__ Maps maps, const bf16* __restrict__ mem0, const bf16* x_in, const bf16* Wq, const bf16* Wk, const bf16* Wv,
             const bf16* Wo, uint32_t zero) {
  extern __shared__ __align__(1024) unsigned char smem_raw[];
  const uint32_t sb = smem_u32(smem_raw);
  const int tid = __shfl_sync(0xffffffffu, (int)threadIdx.x, threadIdx.x & 31);
  const int warp = __shfl_sync(0xffffffffu, tid >> 5, 0), lane = tid & 31;
  const int rank = blockIdx.x & 15;
  const int cl = blockIdx.x >> 4;
  const int bid = cl * 16 + rank;
  const int gi = rank >> 1, a = rank & 1, head = cl * 8 + gi;
  const uint32_t t0 = clk32();
  const uint32_t bar = sb + SM_BAR;
  const uint32_t sl = sb + lane * 16;
  TR_T(trs);
  auto krow = [&](int sp) { const int idx = sp >> 1; const int p = idx < 8 ? ((gi + idx) & 7) : 8; return 288 * a + 32 * p + 16 * (sp & 1); };
  if (tid == 32) atomicAdd(&g_resident, 1u);
  const int ln_r8 = ((bid & 3) * 4 + warp / 3) + (bid >> 2) * 16, ln_w = warp % 3;
  uint4 lnv[6];
  {
    const uint4* src = reinterpret_cast<const uint4*>(x_in + (size_t)(ln_r8 * 8 + (lane >> 2)) * DM) + ln_w * 24 + (lane & 3);
#pragma unroll
    for (int t = 0; t < 6; t++) lnv[t] = __ldg(src + t * 4);
  }
  if (tid >= 96) {
    const int i = tid - 96, idx = i >> 5, t = lane >> 2, j = lane & 3;
    const int p = idx < 8 ? ((gi + idx) & 7) : 8;
    const uint32_t* src = reinterpret_cast<const uint32_t*>(mem0 + t * DM + 288 * a + 32 * p + 2 * j);
    sts128(sb + SM_MEM + i * 16, src[0], src[4], src[8], src[12]);
    if (i < 216) sts128(sb + SM_MB + i * 16, 0, 0, 0, 0);
  }
  PROF0(39);
  if (tid >= 64 && tid < 68) asm volatile("prefetch.tensormap [%0];" :: "l"(&maps.q + (tid - 64)) : "memory");
  if (warp == 0) {
    if (lane == 0) {
      mbar_init(bar + B_AG, 2); mbar_init(bar + B_AG + 8, 1); mbar_init(bar + B_AG + 16, 1); mbar_init(bar + B_AG + 24, 1); mbar_init(bar + B_AG + 32, 2);
      mbar_init(bar + B_XQK, 1); mbar_init(bar + B_XV, 9); mbar_init(bar + B_RS, 2); mbar_init(bar + B_KV, 1); mbar_init(bar + B_L, 1);
      for (int i = 0; i < 5; i++) mbar_init(bar + B_W + i * 8, 1);
      asm volatile("fence.mbarrier_init.release.cluster;" ::: "memory");
      mbar_expect(bar + B_W, 20 * SLOT); mbar_expect(bar + B_W + 8, 16 * SLOT); mbar_expect(bar + B_W + 16, 9 * SLOT);
      mbar_expect(bar + B_W + 24, 5 * 16384); mbar_expect(bar + B_W + 32, 9 * SLOT);
    }
    __syncwarp();
  }
  {
    const int g = lane >> 2, j = lane & 3;
    const uint32_t red = sb + SM_S + (warp / 3) * 256;
    float f[48];
#pragma unroll
    for (int t = 0; t < 6; t++) {
      f[t * 8 + 0] = bflo(lnv[t].x); f[t * 8 + 1] = bfhi(lnv[t].x); f[t * 8 + 2] = bflo(lnv[t].y); f[t * 8 + 3] = bfhi(lnv[t].y);
      f[t * 8 + 4] = bflo(lnv[t].z); f[t * 8 + 5] = bfhi(lnv[t].z); f[t * 8 + 6] = bflo(lnv[t].w); f[t * 8 + 7] = bfhi(lnv[t].w);
    }
    float sum = 0.f;
#pragma unroll
    for (int i = 0; i < 48; i++) sum += f[i];
    sum += __shfl_xor_sync(~0u, sum, 1); sum += __shfl_xor_sync(~0u, sum, 2);
    if (j == 0) sts32(red + g * 16 + ln_w * 4, __float_as_uint(sum));
    PROF0(40);
    __syncthreads();
  if (tid >= 96 && tid < 352 + 32) {
    const int i = tid - 96;
#pragma unroll
    for (int m = 0; m < 4; m++) {
      const char* p = (const char*)(m == 0 ? Wk : m == 1 ? Wv : m == 2 ? Wq : Wo) + ((size_t)bid * 576 + i) * 128;
      asm volatile("prefetch.global.L2 [%0];" :: "l"(p));
      asm volatile("prefetch.global.L2 [%0];" :: "l"(p + 288 * 128));
    }
  }
    uint4 r = lds128(red + g * 16);
    const float mean = (__uint_as_float(r.x) + __uint_as_float(r.y) + __uint_as_float(r.z)) * (1.f / DM);
    float q = 0.f;
#pragma unroll
    for (int i = 0; i < 48; i++) { f[i] -= mean; q = fmaf(f[i], f[i], q); }
    q += __shfl_xor_sync(~0u, q, 1); q += __shfl_xor_sync(~0u, q, 2);
    if (j == 0) sts32(red + 128 + g * 16 + ln_w * 4, __float_as_uint(q));
    __syncthreads();
    r = lds128(red + 128 + g * 16);
    const float rs = rsqrtf((__uint_as_float(r.x) + __uint_as_float(r.y) + __uint_as_float(r.z)) * (1.f / DM) + 1e-5f);
    uint4* dst = g_xnT + ((size_t)(ln_r8 >> 4) * 9 + ln_w * 3) * 1024 + (ln_r8 & 15) * 64 + j * 8 + g;
#pragma unroll
    for (int t = 0; t < 6; t++)
      stg128(dst + (t >> 1) * 1024 + (t & 1) * 32, pack2(f[t * 8] * rs, f[t * 8 + 1] * rs), pack2(f[t * 8 + 2] * rs, f[t * 8 + 3] * rs),
             pack2(f[t * 8 + 4] * rs, f[t * 8 + 5] * rs), pack2(f[t * 8 + 6] * rs, f[t * 8 + 7] * rs));
  }
  PROF0(41);
  __syncthreads();
  if (tid == 352) {
    asm volatile("red.release.gpu.global.add.u32 [%0], 1;" :: "l"(&g_cntX[bid < 4 ? 0 : 32]) : "memory");
  }
  __syncwarp();
  __syncwarp();
  PROF0(42);
  cluster_sync();
  PROF0(43);
  if (warp < 3) {
    if (lane == 0) {
      if (warp != 1) {
        const int m = warp >> 1;
        const CUtensorMap* mp = m ? &maps.q : &maps.k;
        for (int u = 0; u < 10; u++) tma3d(sb + SM_WO + (2 * u + 1 - m) * SLOT, mp, krow(NX + u), head * 2, bar + B_W);
        for (int u = 0; u < 8; u++) tma3d(sb + SM_X + (2 * u + 1 - m) * SLOT, mp, krow(u), head * 2, bar + B_W + 8);
      } else {
        for (int u = 0; u < 9; u++) tma3d(sb + SM_V2 + (4 + u) * SLOT, &maps.v, krow(NV2 + u), head * 2, bar + B_W + 16);
        for (int u = 0; u < 4; u++) tma3d(sb + SM_V2 + u * SLOT, &maps.v, krow(u), head * 2, bar + B_W + 32);
      }
    }
    __syncwarp();
  }

  if (warp < 8) {
    asm volatile("setmaxnreg.inc.sync.aligned.u32 %0;" :: "n"(REG_C));
    const int w = warp;
    const uint32_t wl = sb + (w >> 2) * 2048 + frag_off(lane, w & 3);
    const uint32_t wo = sb + SM_WO + (w >> 1) * 16384 + frag_off(lane, (w & 1) * 2);
    uint32_t Pqk[18 - NX][2][4], Pv[NPV][4];
    uint32_t Xqk[NX][2][4];
#pragma unroll
    for (int u = 0; u < 20; u++) for (int q = 0; q < 4; q++) Pqk[u >> 1][u & 1][q] = 0;
#pragma unroll
    for (int u = 0; u < NPV; u++) for (int q = 0; q < 4; q++) Pv[u][q] = 0;
#pragma unroll
    for (int u = 0; u < 2 * NX; u++) for (int q = 0; q < 4; q++) Xqk[u >> 1][u & 1][q] = 0;
    const uint32_t partner = rank ^ 1;
    const uint32_t pd = __shfl_sync(~0u, mapa(sb, partner) - sb, 0), od = __shfl_sync(~0u, mapa(sb, 2 * w + a) - sb, 0);
    const bool late = STAGGER && w >= 4;
    const uint32_t ag = bar + B_AG + (late ? 8 : 0);

    for (int s = -1; s < NSEG; s++) {
      const uint32_t par = s & 1;
      float q0[4] = {0.f, 0.f, 0.f, 0.f}, k0[4] = {0.f, 0.f, 0.f, 0.f}, q1[4] = {0.f, 0.f, 0.f, 0.f}, k1[4] = {0.f, 0.f, 0.f, 0.f};
      uint4 B[9] = {};
      uint32_t V2[NV2][4];
      auto qk = [&](int idx) {
        const int s0 = 2 * idx, s1 = 2 * idx + 1;
        if (s0 < NX) { mma16816(q0, Xqk[s0][0], B[idx].x, B[idx].y); mma16816(k0, Xqk[s0][1], B[idx].x, B[idx].y); }
        else { mma16816(q0, Pqk[s0 - NX][0], B[idx].x, B[idx].y); mma16816(k0, Pqk[s0 - NX][1], B[idx].x, B[idx].y); }
        if (s1 < NX) { mma16816(q1, Xqk[s1][0], B[idx].z, B[idx].w); mma16816(k1, Xqk[s1][1], B[idx].z, B[idx].w); }
        else { mma16816(q1, Pqk[s1 - NX][0], B[idx].z, B[idx].w); mma16816(k1, Pqk[s1 - NX][1], B[idx].z, B[idx].w); }
      };
      mbar_wait(bar + B_AG, par, t0);
      if (w == 0) { PROF(0); PROFN(24); PROFS(); }
      B[0] = lds128(sl + SM_MEM);
      qk(0);
      ldsm4t(V2[0], wl + SM_V2); ldsm4t(V2[1], wl + SM_V2 + SLOT);
      if (late) mbar_wait(bar + B_AG + 8, par, t0);
      mbar_wait(ag + 8, par, t0);
      if (w == 0) PROF(1);
      B[1] = lds128(sl + SM_MEM + 512); B[2] = lds128(sl + SM_MEM + 1024);
      bool ok = mbar_try(ag + 16, par);
      qk(1);
      if (!ok) mbar_wait(ag + 16, par, t0);
      B[3] = lds128(sl + SM_MEM + 1536); B[4] = lds128(sl + SM_MEM + 2048);
      ok = mbar_try(ag + 24, par);
      qk(2);
      ldsm4t(V2[2], wl + SM_V2 + 2 * SLOT); ldsm4t(V2[3], wl + SM_V2 + 3 * SLOT);
      qk(3);
      if (!ok) mbar_wait(ag + 24, par, t0);
      if (w == 0) PROF(2);
      B[5] = lds128(sl + SM_MEM + 2560); B[6] = lds128(sl + SM_MEM + 3072);
      ok = mbar_try(bar + B_AG + 32, par);
      qk(4);
      ldsm4t(V2[4], wl + SM_V2 + 4 * SLOT); ldsm4t(V2[5], wl + SM_V2 + 5 * SLOT);
      qk(5);
      if (!ok) mbar_wait(bar + B_AG + 32, par, t0);
      if (w == 0) PROF(3);
      B[7] = lds128(sl + SM_MEM + 3584); B[8] = lds128(sl + SM_MEM + 4096);
      qk(6);
      ldsm4t(V2[6], wl + SM_V2 + 6 * SLOT); ldsm4t(V2[7], wl + SM_V2 + 7 * SLOT);
      qk(7);
      if (late) bar_arrive(BAR_AB, 256);
      qk(8);
      const uint32_t pq0 = pack2(q0[0] + q1[0], q0[1] + q1[1]);
      {
        const uint32_t c0 = movmat(pq0), c1 = movmat(pack2(q0[2] + q1[2], q0[3] + q1[3]));
        const uint32_t c2 = movmat(pack2(k0[0] + k1[0], k0[1] + k1[1])), c3 = movmat(pack2(k0[2] + k1[2], k0[3] + k1[3]));
        const bool swp = sl & 128;
        const uint32_t y0 = swp ? c2 : c0, y1 = swp ? c3 : c1, y2 = swp ? c0 : c2, y3 = swp ? c1 : c3;
        if (s >= 0) st_async16(sl + (pd + w * 512 + SM_XQK), y0, y1, y2, y3, bar + pd + B_XQK);
        sts128(sl + (w * 512 + SM_OQK), y0, y1, y2, y3);
        bar_arrive(BAR_OQK, NTHREADS);
      }
      if (w == 0) PROF(4);
      if (w == 4) PROF(14);
      ldsm4t(V2[8], wl + SM_V2 + 8 * SLOT);
      if (STAGGER && !late) bar_sync(BAR_AB, 256);
      const float vz = __uint_as_float(pq0 & zero);
      float v[4][4] = {{vz, 0.f, 0.f, 0.f}, {vz, 0.f, 0.f, 0.f}, {vz, 0.f, 0.f, 0.f}, {vz, 0.f, 0.f, 0.f}};
      uint32_t WO[16][4];
      if (s == 0) mbar_wait(bar + B_W + 24, 0, t0);
#pragma unroll
      for (int idx = 0; idx < 9; idx++) {
        const int s0 = 2 * idx, s1 = 2 * idx + 1;
        if (s0 < NV2) mma16816(v[s0 & 3], V2[s0], B[idx].x, B[idx].y); else mma16816(v[s0 & 3], Pv[s0 - NV2], B[idx].x, B[idx].y);
        if (s1 < NV2) mma16816(v[s1 & 3], V2[s1], B[idx].z, B[idx].w); else mma16816(v[s1 & 3], Pv[s1 - NV2], B[idx].z, B[idx].w);
        if (idx >= 9 - WEARLY) ldsm4t(WO[idx - (9 - WEARLY)], wo + (idx - (9 - WEARLY)) * 2048);
      }
      {
        const uint32_t vo0 = pack2((v[0][0] + v[1][0]) + (v[2][0] + v[3][0]), (v[0][1] + v[1][1]) + (v[2][1] + v[3][1]));
        const uint32_t vo1 = pack2((v[0][2] + v[1][2]) + (v[2][2] + v[3][2]), (v[0][3] + v[1][3]) + (v[2][3] + v[3][3]));
        const uint32_t l8 = (sl - sb) >> 1;
        if (s >= 0) st_async8(l8 + (sb + pd + w * 256 + SM_XV), vo0, vo1, bar + pd + B_XV);
        sts64(l8 + (sb + w * 256 + SM_OV), vo0, vo1);
        __syncwarp();
        mbar_arrive_if(bar + B_XV, sl == sb && s >= 0);
      }
      if (w == 0) PROF(5);
      if (s == NSEG - 1) break;
#pragma unroll
      for (int u = WEARLY; u < 16; u++) ldsm4t(WO[u], dep(u >= 8 ? wo ^ 32 : wo, WO[(u < 16 - WLATE ? u : 16 - WLATE) - 1][0], zero) + (u & 7) * 2048);
      if (w == 0) PROF(6);
      bar_sync(BAR_O, NTHREADS);
      {
        float m0[4] = {0.f, 0.f, 0.f, 0.f}, m1[4] = {0.f, 0.f, 0.f, 0.f}, m2[4] = {0.f, 0.f, 0.f, 0.f}, m3[4] = {0.f, 0.f, 0.f, 0.f};
        uint32_t ob[4][4];
        bool okl = false;
#pragma unroll
        for (int u = 0; u < 4; u++) ldsm4t(ob[u], sl + SM_O + u * 512);
#pragma unroll
        for (int u = 0; u < 3; u++) {
          mma16816(m0, WO[2 * u], ob[u][0], ob[u][1]);     mma16816(m1, WO[8 + 2 * u], ob[u][0], ob[u][1]);
          mma16816(m2, WO[2 * u + 1], ob[u][2], ob[u][3]); mma16816(m3, WO[8 + 2 * u + 1], ob[u][2], ob[u][3]);
          if (u == 0) okl = mbar_try(bar + B_L, par);
        }
        if (!okl) mbar_wait(bar + B_L, par, t0);
        const uint2 iv = lds64(sb + SM_INV + ((sl >> 1) & 24));
        mma16816(m0, WO[6], ob[3][0], ob[3][1]); mma16816(m1, WO[14], ob[3][0], ob[3][1]);
        mma16816(m2, WO[7], ob[3][2], ob[3][3]); mma16816(m3, WO[15], ob[3][2], ob[3][3]);
        const float i0 = __uint_as_float(iv.x), i1 = __uint_as_float(iv.y);
        const uint32_t c0 = movmat(pack2((m0[0] + m2[0]) * i0, (m0[1] + m2[1]) * i1)), c1 = movmat(pack2((m0[2] + m2[2]) * i0, (m0[3] + m2[3]) * i1));
        const uint32_t c2 = movmat(pack2((m1[0] + m3[0]) * i0, (m1[1] + m3[1]) * i1)), c3 = movmat(pack2((m1[2] + m3[2]) * i0, (m1[3] + m3[3]) * i1));
        if (w == gi) {
          sts128(sl + SM_RS + gi * 576, c0, c1, c2, c3);
          __syncwarp();
          mbar_arrive_if(bar + B_RS, sl == sb && s >= 0);
        } else if (s >= 0) {
          st_async16(sl + (od + SM_RS + gi * 576), c0, c1, c2, c3, bar + od + B_RS);
        }
      }
      if (w == 0) PROF(10);
      if (w == 4) PROF(15);
      if (s < 0) {
        if (w == 3) PROF1(44);
        mbar_wait(bar + B_W, 0, t0);
#pragma unroll
        for (int u = 0; u < 20; u++) ldsm4t(Pqk[u >> 1][u & 1], wl + SM_WO + u * SLOT);
        mbar_wait(bar + B_W + 16, 0, t0);
#pragma unroll
        for (int u = 0; u < NPV; u++) ldsm4t(Pv[u], wl + SM_V2 + (4 + u) * SLOT);
        if (w == 3) PROF1(45);
        bar_sync(BAR_C, 256);
        if (w == 0) {
          if (lane < 5) tma3d(sb + SM_V2 + (4 + lane) * SLOT, &maps.v, krow(4 + lane), head * 2, bar + B_W + 32);
          else if (lane < 10) tma2d(sb + SM_WO + (lane - 5) * 16384, &maps.o, 288 * a + 64 * (lane - 5), head * DH, bar + B_W + 24);
          __syncwarp();
        }
        bar_arrive(BAR_ALL, NTHREADS);
        mbar_wait(bar + B_W + 8, 0, t0);
        mbar_wait(bar + B_W + 32, 0, t0);
      }
#pragma unroll
      for (int u = 0; u < 2 * NX; u++) {
        if (u == 6) mbar_wait(bar + B_RS, par, t0);
        ldsm4t(Xqk[u >> 1][u & 1], (u < 1 ? wl : dep(wl, Xqk[(u - 1) >> 1][(u - 1) & 1][0], zero)) + SM_X + u * SLOT);
      }
      if (w == 0) PROF(11);
    }
    __syncwarp();
    cluster_sync();
  } else {
    asm volatile("setmaxnreg.dec.sync.aligned.u32 %0;" :: "n"(REG_A));
    const int x = warp - 8;
    const int g = lane >> 2, j = lane & 3;
    const uint32_t sa = sb + SM_S + x * 512 + (32 * j + 4 * (g >> 1) + (g & 1)) * 4;
    const uint32_t sq = sl + (lane & 8);
    if (x < 2) {
      bar_arrive(BAR_ALL, NTHREADS);
      for (int s = -1; s < NSEG - 1; s++) {
        const uint32_t par = s & 1;
        uint4 R[8];
        if (s == 0) mbar_wait(bar + B_W + 24, 0, t0);
        mbar_wait(bar + B_KV, par, t0);
#pragma unroll
        for (int u = 0; u < 8; u++) R[u] = lds128(sl + SM_KX + x * 4096 + u * 512);
        float c0[4] = {0.f, 0.f, 0.f, 0.f}, c1[4] = {0.f, 0.f, 0.f, 0.f}, c2[4] = {0.f, 0.f, 0.f, 0.f}, c3[4] = {0.f, 0.f, 0.f, 0.f};
        bar_sync(BAR_OQK, NTHREADS);
        {
          uint2 b[8];
#pragma unroll
          for (int u = 0; u < 8; u++) b[u] = lds64(sq + SM_OQK + u * 512);
          mmaq(c0, R[0], b[0].x, b[0].y); mmaq(c1, R[1], b[1].x, b[1].y); mmaq(c2, R[2], b[2].x, b[2].y); mmaq(c3, R[3], b[3].x, b[3].y);
          mmaq(c0, R[4], b[4].x, b[4].y); mmaq(c1, R[5], b[5].x, b[5].y); mmaq(c2, R[6], b[6].x, b[6].y); mmaq(c3, R[7], b[7].x, b[7].y);
        }
        if (x == 0) PROF(16);
        mbar_wait(bar + B_XQK, par, t0);
        if (x == 0) PROF(17);
        {
          uint2 b[8];
#pragma unroll
          for (int u = 0; u < 8; u++) b[u] = lds64(sq + SM_XQK + u * 512);
          mmaq(c0, R[0], b[0].x, b[0].y); mmaq(c1, R[1], b[1].x, b[1].y); mmaq(c2, R[2], b[2].x, b[2].y); mmaq(c3, R[3], b[3].x, b[3].y);
          mmaq(c0, R[4], b[4].x, b[4].y); mmaq(c1, R[5], b[5].x, b[5].y); mmaq(c2, R[6], b[6].x, b[6].y); mmaq(c3, R[7], b[7].x, b[7].y);
        }
        sts32(sa, __float_as_uint((c0[0] + c1[0]) + (c2[0] + c3[0])));
        sts32(sa + 64, __float_as_uint((c0[1] + c1[1]) + (c2[1] + c3[1])));
        sts32(sa + 8, __float_as_uint((c0[2] + c1[2]) + (c2[2] + c3[2])));
        sts32(sa + 72, __float_as_uint((c0[3] + c1[3]) + (c2[3] + c3[3])));
        if (x == 0) PROF(18);
        uint32_t WX[8][4];
        softmax_pv<true>(s, x, sb, sl, bar, lane, a, head, t0, WX, x == 0);
        {
          float m0[4] = {0.f, 0.f, 0.f, 0.f}, m1[4] = {0.f, 0.f, 0.f, 0.f}, m2[4] = {0.f, 0.f, 0.f, 0.f}, m3[4] = {0.f, 0.f, 0.f, 0.f};
          uint32_t ob[4][4];
#pragma unroll
          for (int u = 0; u < 4; u++) ldsm4t(ob[u], sl + SM_O + u * 512);
          const int ln = opaque(lane);
          const uint32_t r_rs2 = mapa(sb + SM_RS + gi * 576 + (32 + (ln & 3)) * 16 + x * 8, 2 * (ln >> 2) + a), r_rsb2 = mapa(bar + B_RS, 2 * (ln >> 2) + a);
          mma16816(m0, WX[0], ob[0][0], ob[0][1]); mma16816(m1, WX[1], ob[0][2], ob[0][3]);
          mma16816(m2, WX[2], ob[1][0], ob[1][1]); mma16816(m3, WX[3], ob[1][2], ob[1][3]);
          mma16816(m0, WX[4], ob[2][0], ob[2][1]); mma16816(m1, WX[5], ob[2][2], ob[2][3]);
          mma16816(m2, WX[6], ob[3][0], ob[3][1]); mma16816(m3, WX[7], ob[3][2], ob[3][3]);
          mbar_wait(bar + B_L, par, t0);
          const uint2 iv = lds64(sb + SM_INV + (ln & 3) * 8);
          const float i0 = __uint_as_float(iv.x), i1 = __uint_as_float(iv.y);
          const uint32_t d0 = movmat(pack2(((m0[0] + m1[0]) + (m2[0] + m3[0])) * i0, ((m0[1] + m1[1]) + (m2[1] + m3[1])) * i1));
          const uint32_t d1 = movmat(pack2(((m0[2] + m1[2]) + (m2[2] + m3[2])) * i0, ((m0[3] + m1[3]) + (m2[3] + m3[3])) * i1));
          if (s >= 0) st_async8(r_rs2, d0, d1, r_rsb2);
        }
        if (x == 0) PROF(19);
        reduce_exchange(x, gi, a, s, sb, bar, lane, t0, x == 0, bid);
      }
      bar_sync(BAR_OQK, NTHREADS);
    } else {
      const unsigned epoch = g_epoch + 1;
      const uint4* kx_g = g_Kf + (size_t)head * 128 * 256;
      const uint4* vx_g = g_Vf + (size_t)head * NSEG * 512;
      const int hh = x - 2;
      const uint32_t sm_ = sa - hh * 512 + hh * 8;
      uint4* const km_ptr = g_Kmf + (size_t)head * NSEG * 128 + hh * 64 + lane;
      if (x == 2) bar_arrive(BAR_ALL, NTHREADS);
      for (int s = -1; s < NSEG; s++) {
        const uint32_t par = s & 1;
        uint2 Q[4], K[4], oq[4], okk[4];
        if (s < NSEG - 1) mbar_wait(bar + B_KV, par, t0);
        bar_sync(BAR_OQK, NTHREADS);
#pragma unroll
        for (int u = 0; u < 4; u++) { Q[u] = lds64(sq + SM_OQK + (hh * 4 + u) * 512); K[u] = lds64((sq ^ 8) + SM_OQK + (hh * 4 + u) * 512); }
        mbar_wait(bar + B_XQK, par, t0);
        float c0[4] = {0.f, 0.f, 0.f, 0.f}, c1[4] = {0.f, 0.f, 0.f, 0.f}, c2[4] = {0.f, 0.f, 0.f, 0.f}, c3[4] = {0.f, 0.f, 0.f, 0.f};
#pragma unroll
        for (int u = 0; u < 4; u++) { oq[u] = lds64(sq + SM_XQK + (hh * 4 + u) * 512); okk[u] = lds64((sq ^ 8) + SM_XQK + (hh * 4 + u) * 512); }
#pragma unroll
        for (int u = 0; u < 4; u++) {
          Q[u].x = hadd2bf(Q[u].x, oq[u].x); Q[u].y = hadd2bf(Q[u].y, oq[u].y); K[u].x = hadd2bf(K[u].x, okk[u].x); K[u].y = hadd2bf(K[u].y, okk[u].y);
        }
#pragma unroll
        for (int u = 0; u < 4; u += 2) {
          mma1688(c0, K[u].x, K[u].y, Q[u].x);
          mma1688(c1, K[u].x, K[u].y, Q[u].y);
          mma1688(c2, K[u + 1].x, K[u + 1].y, Q[u + 1].x);
          mma1688(c3, K[u + 1].x, K[u + 1].y, Q[u + 1].y);
        }
        sts32(sm_, __float_as_uint((c0[0] + c1[2]) + (c2[0] + c3[2])));
        sts32(sm_ + 64, __float_as_uint((c0[1] + c1[3]) + (c2[1] + c3[3])));
        uint32_t dummy[8][4];
        if (s < NSEG - 1) softmax_pv<false>(s, x, sb, sl, bar, lane, a, head, t0, dummy, 0);
        if (a == 0 && s >= 0) {
          km_ptr[(size_t)s * 128] = make_uint4(K[0].x, K[0].y, K[1].x, K[1].y);
          km_ptr[(size_t)s * 128 + 32] = make_uint4(K[2].x, K[2].y, K[3].x, K[3].y);
        }
        if (s == NSEG - 1) break;
        if (x == 2) {
          reduce_exchange(x, gi, a, s, sb, bar, lane, t0, 0, bid);
          if (lane == 0) mbar_expect(bar + B_RS, RS_BYTES);
        } else {
          if (lane == 0 && s >= 0 && s + 1 < NSEG - 1) {
            mbar_expect(bar + B_KV, 16384);
            bulk_g2s(sb + SM_KX, kx_g + (size_t)(s + 1) * 512, 8192, bar + B_KV);
            bulk_g2s(sb + SM_VX, vx_g + (size_t)(s + 1) * 512, 8192, bar + B_KV);
          }
          __syncwarp();
          mbar_wait(bar + B_RS, par, t0);
          if (lane == 0) {
            const int nb = s < 0 ? 0 : 1024;
            mbar_expect(bar + B_AG + 8, nb); mbar_expect(bar + B_AG + 16, nb); mbar_expect(bar + B_AG + 24, nb); mbar_expect(bar + B_AG + 32, s < 0 ? 0 : 960);
            mbar_expect(bar + B_XQK, 4096); mbar_expect(bar + B_XV, 2048);
            if (a == 0 && (s & 3) == 0 && s > 0) { st_release(&g_memflag[head * 8], epoch * 64 + s); if (bid == 0) TR_LOG(9 | (((s - 1) >> 2) << 24), trs, trs); }
            if ((s & 3) == 2 && s + 2 < NSEG) {
              while (ld_acquire(&g_kvflag[((s + 2) >> 2) * 64 + head]) != epoch) { if (timed_out(t0)) break; }
              while (ld_acquire(&g_kvflag[((s + 2) >> 2) * 64 + 32 + head]) != epoch) { if (timed_out(t0)) break; }
              asm volatile("fence.proxy.async.global;" ::: "memory");
              asm volatile("cp.async.bulk.prefetch.L2.global [%0], 32768;" :: "l"(kx_g + (size_t)(s + 2) * 512) : "memory");
              asm volatile("cp.async.bulk.prefetch.L2.global [%0], 32768;" :: "l"(vx_g + (size_t)(s + 2) * 512) : "memory");
            }
          }
          if (s < 0) {
            __syncwarp();
            bar_sync(BAR_ALL, NTHREADS);
            if (lane == 0) {
              while (ld_acquire(&g_kvflag[head]) != epoch) { if (timed_out(t0)) break; __nanosleep(100); }
              while (ld_acquire(&g_kvflag[32 + head]) != epoch) { if (timed_out(t0)) break; __nanosleep(100); }
              asm volatile("fence.proxy.async.global;" ::: "memory");
              mbar_expect(bar + B_KV, 16384);
              bulk_g2s(sb + SM_KX, kx_g, 8192, bar + B_KV);
              bulk_g2s(sb + SM_VX, vx_g, 8192, bar + B_KV);
            }
          }
        }
        __syncwarp();
      }
    }
    {
      mbar_wait(bar + B_XV, (NSEG - 1) & 1, t0);
      const uint32_t lv = sb + x * 512 + lane * 8;
      const uint2 ov0 = lds64(lv + SM_OV), xv0 = lds64(lv + SM_XV), ov1 = lds64(lv + SM_OV + 256), xv1 = lds64(lv + SM_XV + 256);
      if (a == 0) g_Vmf[((size_t)head * NSEG + NSEG - 1) * 128 + x * 32 + lane] = make_uint4(hadd2bf(ov0.x, xv0.x), hadd2bf(ov0.y, xv0.y), hadd2bf(ov1.x, xv1.x), hadd2bf(ov1.y, xv1.y));
      bar_sync(BAR_S, 128);
      if (x == 3 && a == 0 && lane == 0) { st_release(&g_memflag[head * 8], (g_epoch + 1) * 64 + 64); if (bid == 0) TR_LOG(9 | (15 << 24), trs, trs); }
    }
    __syncwarp();
    cluster_sync();
  }
}
}
__device__ __align__(1024) uint4 g_hnT[NRB * 9 * 1024];
__device__ __align__(1024) uint4 g_oT[NRB * 64 * 1024];
__device__ __align__(1024) uint4 g_gT[NRB * 72 * 1024];
constexpr int MAXSPLIT = 8;
__device__ __align__(1024) uint4 g_p1[MAXSPLIT * 256 * 18 * 32];
__device__ __align__(1024) uint4 g_p2[MAXSPLIT * 256 * 18 * 32];
__device__ __align__(1024) uint4 g_hT[256 * 18 * 32];

__global__ void gate_kernel() {
  const uint32_t t0 = clk32();
  const unsigned need = (g_epoch + 1) * 64u;
  while ((int)(ld_acquire(&g_resident) - need) < 0) { if (timed_out(t0)) break; }
}
namespace mega {
constexpr int NS = 5;
constexpr int SM_B = 0, SM_A = 9 * 16384, SM_BAR = SM_A + NS * 16384;
constexpr int B_FA = 0, B_EA = NS * 8, B_FB = 2 * NS * 8, B_EB = B_FB + 96, B_D = B_EB + 24, B_TK = B_D + 32, B_QF = B_TK + 32, B_QE = B_QF + 16,
              B_PD = B_QE + 16, B_PE = B_PD + 16;
constexpr int SM_DESC = SM_BAR + 512;
constexpr int SM_TQ = SM_DESC + 64;
constexpr int SM_TK = SM_TQ + 32;
constexpr int SM_PUB = SM_TK + 16;
constexpr int SM_RED = SM_PUB + 16;
constexpr int SM_TOTAL = SM_RED + 256;
enum { T_K = 0, T_V = 1, T_QA = 2, T_OP = 3, T_F1 = 4, T_F2 = 5, T_END = 6 };
#define GRP_TABLE 0x1122224ull
#define GRP_COUNT 9
#undef GRP_TABLE
#define GRP_TABLE 0x112222222ull
constexpr int NGRP = GRP_COUNT;
__device__ __forceinline__ int grp_n(int g) { return (int)((GRP_TABLE >> (4 * g)) & 15); }
__device__ __forceinline__ int grp_rb0(int g) { int r = 0; for (int i = 0; i < g; i++) r += grp_n(i); return r; }
constexpr int TPG = 16 + 18 + 18 + 18;
constexpr int NTASK = 32 + NGRP * TPG - 16;
constexpr int NWTASK = 2048;
constexpr int SPL = 6;
constexpr int REG_C = 200, REG_P = 104;
static_assert(2 * REG_C + REG_P <= 504, "register pool");

__device__ unsigned g_ticket, g_wticket;
constexpr int PAD = 32;
__device__ unsigned g_cntO[NRB * 8 * PAD], g_cntP1[NRB * PAD], g_cntH[NRB * PAD], g_cntG[NRB * 8 * PAD], g_cntP2[NRB * PAD], g_done;

template <int B> struct IntC { static constexpr int value = B; };
__device__ __forceinline__ void red_release(unsigned* p) { asm volatile("red.release.gpu.global.add.u32 [%0], 1;" :: "l"(p) : "memory"); }
__device__ __forceinline__ void wait_cnt(const unsigned* p, unsigned need, int far, uint32_t t0) {
  while (true) {
    const int d = (int)(ld_relaxed(p) - need);
    if (d >= 0) break;
    if (timed_out(t0)) break;
    __nanosleep(d <= -far ? 1000 : 100);
  }
  (void)ld_acquire(p);
}
__device__ __forceinline__ float gelu_tanh(float z) {
  const float u = z * fmaf(z * z, 0.044715f * 0.7978845608028654f, 0.7978845608028654f);
  float t; asm("tanh.approx.f32 %0, %1;" : "=f"(t) : "f"(u));
  const float hz = 0.5f * z;
  return fmaf(hz, t, hz);
}
__device__ __forceinline__ void acc8(float (&f)[8], const uint4& v) {
  f[0] += bflo(v.x); f[1] += bfhi(v.x); f[2] += bflo(v.y); f[3] += bfhi(v.y);
  f[4] += bflo(v.z); f[5] += bfhi(v.z); f[6] += bflo(v.w); f[7] += bfhi(v.w);
}

__device__ __forceinline__ void arrive2_if(uint32_t local, uint32_t pd, int p, int cnt) {
  asm volatile("{ .reg .pred q; setp.ne.b32 q, %2, 0; @q mbarrier.arrive.shared::cta.b64 _, [%0], %3; @q mbarrier.arrive.shared::cluster.b64 _, [%1], %3; }"
    :: "r"(local), "r"(local + pd), "r"(p), "r"(cnt) : "memory");
}
__device__ __forceinline__ void bulk_mc(uint32_t dst, const void* src, uint32_t bytes, uint32_t bar) {
  asm volatile("cp.async.bulk.shared::cluster.global.mbarrier::complete_tx::bytes.multicast::cluster [%0], [%1], %2, [%3], %4;"
    :: "r"(dst), "l"(src), "r"(bytes), "r"(bar), "h"((uint16_t)3) : "memory");
}
__device__ __forceinline__ int op_kb0(int kc) { return kc < 2 ? 12 * kc : 4 + 10 * kc; }
__device__ __forceinline__ int task_nkb(int type, int kc) { return type == T_OP ? (kc < 2 ? 12 : 10) : type == T_F2 ? 12 : 9; }

struct Maps { CUtensorMap m[6]; };

__global__ void __launch_bounds__(384, 1)
mega_kernel(const __grid_constant__ Maps maps, const bf16* __restrict__ x, const bf16* __restrict__ b1, const bf16* __restrict__ b2,
            bf16* __restrict__ out) {
  extern __shared__ __align__(1024) unsigned char smem_raw[];
  const uint32_t sb = smem_u32(smem_raw);
  const int tid = threadIdx.x, wg = __shfl_sync(~0u, tid >> 7, 0), lane = tid & 31, w = __shfl_sync(~0u, (tid >> 5) & 3, 0);
  const uint32_t bar = sb + SM_BAR;
  const uint32_t t0 = clk32();
  if (tid == 0) {
    for (int i = 0; i < NS; i++) { mbar_init(bar + B_FA + i * 8, 1); mbar_init(bar + B_EA + i * 8, 8); }
    for (int i = 0; i < 12; i++) mbar_init(bar + B_FB + i * 8, 1);
    for (int i = 0; i < 3; i++) mbar_init(bar + B_EB + i * 8, 4);
    for (int i = 0; i < 4; i++) mbar_init(bar + B_D + i * 8, 1);
    for (int i = 0; i < 4; i++) mbar_init(bar + B_TK + i * 8, 1);
    for (int i = 0; i < 2; i++) { mbar_init(bar + B_QF + i * 8, 1); mbar_init(bar + B_QE + i * 8, 1); mbar_init(bar + B_PD + i * 8, 4); mbar_init(bar + B_PE + i * 8, 1); }
    asm volatile("fence.mbarrier_init.release.cluster;" ::: "memory");
  }
  const int rank = blockIdx.x & 1;
  const uint32_t pd = __shfl_sync(~0u, mapa(sb, rank ^ 1) - sb, 0);
  const unsigned ep0 = *(volatile unsigned*)&g_epoch;
  const unsigned epoch = ep0 + 1;
  __syncthreads();
  asm volatile("barrier.cluster.arrive.relaxed.aligned; barrier.cluster.wait.aligned;" ::: "memory");
  if (wg == 2) {
    asm volatile("setmaxnreg.dec.sync.aligned.u32 %0;" :: "n"(REG_P));
    if (w == 0) {
      if (lane == 0) {
        int st = 0, ph = 1, seq = 0, qi = 0;
        auto pop = [&]() {
          mbar_wait(bar + B_QF + (qi & 1) * 8, (qi >> 1) & 1, t0);
          const uint4 e = lds128(sb + SM_TQ + (qi & 1) * 16);
          mbar_arrive(bar + B_QE + (qi & 1) * 8);
          qi++;
          return e;
        };
        while (true) {
          const uint4 e = pop();
          const int type = e.x & 255;
          if (type == T_END) break;
          const int sl = (e.x >> 8) & 255, kc = (e.x >> 16) & 255, rb = e.x >> 24;
          sts128(sb + SM_DESC + (seq & 3) * 16, e.x, e.y | st | (ph << 8), e.z, 0);
          mbar_arrive(bar + B_D + (seq & 3) * 8);
          seq++;
          const int nkb = task_nkb(type, kc), kb0 = type == T_OP ? op_kb0(kc) : kc * 12;
          const uint4* A = type <= T_QA ? g_xnT : type == T_OP ? g_oT : type == T_F1 ? g_hnT : g_gT;
          const int ktot = type == T_OP ? 64 : type == T_F2 ? 72 : 9;
          const uint4* src = A + ((size_t)rb * ktot + kb0) * 1024 + rank * 512;
          for (int kb = 0; kb < nkb; kb++) {
            mbar_wait(bar + B_EA + st * 8, ph, t0);
            mbar_expect(bar + B_FA + st * 8, 16384);
            bulk_mc(sb + SM_A + st * 16384 + rank * 8192, src + kb * 1024, 8192, bar + B_FA + st * 8);
            if (++st == NS) { st = 0; ph ^= 1; }
          }
          if (type == T_QA) {
            for (int q = 0; q < 5; q++) {
              if (q == 2) pop();
              mbar_wait(bar + B_EA + st * 8, ph, t0);
              const uint32_t fa = bar + B_FA + st * 8, dst = sb + SM_A + st * 16384;
              mbar_expect(fa, 16384);
              const size_t so = (size_t)sl * NSEG + rb * 4;
              if (q < 2) bulk_g2s(dst, g_Kf + so * 512 + q * 1024, 16384, fa);
              else if (q > 2) bulk_g2s(dst, g_Vf + so * 512 + (q - 3) * 1024, 16384, fa);
              else { bulk_g2s(dst, g_Kmf + so * 128, 8192, fa); bulk_g2s(dst + 8192, g_Vmf + so * 128, 8192, fa); }
              if (++st == NS) { st = 0; ph ^= 1; }
            }
          }
        }
        for (int i = 0; i < 2; i++) {
          sts128(sb + SM_DESC + (seq & 3) * 16, T_END, i, 0, 0);
          mbar_arrive(bar + B_D + (seq & 3) * 8);
          seq++;
        }
      }
      __syncwarp();
      asm volatile("barrier.cluster.arrive.relaxed.aligned; barrier.cluster.wait.aligned;" ::: "memory");
    } else if (w == 1) {
      if (lane == 0) {
        uint32_t fbph = 0, ebph = 1;
        int qi = 0, tk = 0, tiles = 0, pubs = 0, pub0 = 0, pub1 = 0;
        const unsigned tbase = ep0 * (unsigned)(NTASK + gridDim.x / 2);
        auto service = [&]() {
          bool any = false;
          if (mbar_test(bar + B_PD, pub0 & 1)) {
            const uint2 p = lds64(sb + SM_PUB);
            mbar_arrive(bar + B_PE);
            red_release(reinterpret_cast<unsigned*>(((unsigned long long)p.y << 32) | p.x));
            pub0++; pubs++; any = true;
          }
          if (mbar_test(bar + B_PD + 8, pub1 & 1)) {
            const uint2 p = lds64(sb + SM_PUB + 8);
            mbar_arrive(bar + B_PE + 8);
            red_release(reinterpret_cast<unsigned*>(((unsigned long long)p.y << 32) | p.x));
            pub1++; pubs++; any = true;
          }
          return any;
        };
        auto can_post = [&]() { return qi == 0 || mbar_test(bar + B_QE + ((qi - 1) & 1) * 8, ((qi - 1) >> 1) & 1); };
        auto post = [&](uint32_t x, uint32_t y, uint32_t z) {
          sts128(sb + SM_TQ + (qi & 1) * 16, x, y, z, 0);
          mbar_arrive(bar + B_QF + (qi & 1) * 8);
          qi++;
        };
        while (true) {
          unsigned task;
          if (rank == 0) {
            task = atomicAdd(&g_ticket, 1u) - tbase;
            asm volatile("st.async.shared::cluster.mbarrier::complete_tx::bytes.b32 [%0], %1, [%2];"
              :: "r"(sb + SM_TK + (tk & 3) * 4 + pd), "r"(task), "r"(bar + B_TK + (tk & 3) * 8 + pd) : "memory");
          } else {
            mbar_expect(bar + B_TK + (tk & 3) * 8, 4);
            while (!mbar_test(bar + B_TK + (tk & 3) * 8, (tk >> 2) & 1)) { service(); if (timed_out(t0)) break; }
            asm volatile("ld.shared.b32 %0, [%1];" : "=r"(task) : "r"(sb + SM_TK + (tk & 3) * 4) : "memory");
          }
          tk++;
          if (task >= (unsigned)NTASK) break;
          int type, sl, kc = 0, rb0, n;
          if (task < 32) { type = rank; sl = task; rb0 = 0; n = NRB; }
          else {
            int g = 0, r = task - 32, stg = 0;
            for (int i = -3;; ) {
              g = i + 3 - stg;
              const int c = (g >= 0 && g < NGRP) ? (stg == 0 ? (g == NGRP - 1 ? 0 : 16) : 18) : 0;
              if (r < c) break;
              r -= c;
              if (++stg == 4) { stg = 0; i++; }
            }
            type = T_QA + stg;
            if (stg & 1) { kc = r / 3; sl = r % 3; } else sl = r;
            sl = 2 * sl + rank;
            rb0 = grp_rb0(g); n = grp_n(g);
            if (stg == 0 && g == NGRP - 2) n += grp_n(NGRP - 1);
          }
          const bool narrow = type == T_OP || type == T_F2;
          const int nkb = task_nkb(type, kc), kb0 = type == T_OP ? op_kb0(kc) : kc * 12;
          const CUtensorMap* mp = &maps.m[type];
          auto load_third = [&](int th) {
            if (narrow) {
              for (int kb = th * 4; kb < th * 4 + 4 && kb < nkb; kb++) {
                const uint32_t fb = bar + B_FB + kb * 8, dst = sb + SM_B + kb * 12288;
                mbar_expect(fb, 12288);
                for (int p = 0; p < 3; p++) tma5d(dst + p * 4096, mp, sl * 96 + p * 32, (kb0 + kb) * 2, fb);
              }
            } else {
              for (int kb = th * 3; kb < th * 3 + 3; kb++) {
                const uint32_t fb = bar + B_FB + kb * 8, dst = sb + SM_B + kb * 16384;
                mbar_expect(fb, 16384);
                if (type <= T_QA) { tma2d(dst, mp, sl * 128, kb * 64, fb); tma2d(dst + 8192, mp, sl * 128 + 64, kb * 64, fb); }
                else { tma5d(dst, mp, sl * 128, kb * 2, fb); tma5d(dst + 8192, mp, sl * 128 + 64, kb * 2, fb); }
              }
            }
          };
          auto deps_ready = [&](int rb, bool mem) -> bool {
            if (mem) return (int)(ld_acquire(&g_memflag[sl * 8]) - (epoch * 64 + rb * 4 + 4)) >= 0;
            if (type == T_QA) return ld_acquire(&g_kvflag[rb * 64 + sl]) == epoch && ld_acquire(&g_kvflag[rb * 64 + 32 + sl]) == epoch;
            if (type == T_OP) return (int)(ld_acquire(&g_cntO[(rb * 8 + kc) * PAD]) - epoch * (nkb >> 1)) >= 0;
            if (type == T_F1) return (int)(ld_acquire(&g_cntH[rb * PAD]) - epoch * 64) >= 0;
            if (type == T_F2) return (int)(ld_acquire(&g_cntG[(rb * 8 + kc) * PAD]) - epoch * 6) >= 0;
            return rb >= 2 || (rb == 0 ? (int)(ld_acquire(&g_cntX[0]) - epoch * 4) >= 0 : (int)(ld_acquire(&g_cntX[32]) - epoch * 60) >= 0);
          };
          int th = 0, t = 0;
          bool mem = false, rdy = false;
          while (th < 3 || t < n) {
            bool prog = service();
            if (th < 3 && mbar_test(bar + B_EB + th * 8, ebph)) { load_third(th++); prog = true; }
            if (t < n) {
              const int rb = rb0 + t;
              if (!rdy && deps_ready(rb, mem)) {
                rdy = true;
                if (type > T_V || t < 2) asm volatile("fence.proxy.async.global;" ::: "memory");
              }
              if (rdy && can_post()) {
                post(type | (sl << 8) | (kc << 16) | (rb << 24), ((t == n - 1) << 16) | ((t < 2) << 17), fbph);
                rdy = false; prog = true;
                if (type == T_QA && !mem) { mem = true; tiles++; } else { if (type != T_QA) tiles++; mem = false; t++; }
              }
            }
            if (!prog) { if (timed_out(t0)) break; __nanosleep(rdy || t >= n ? 20 : 80); }
          }
          fbph ^= (1u << nkb) - 1; ebph ^= 1;
        }
        while (!can_post()) { service(); if (timed_out(t0)) break; }
        post(T_END, 0, 0);
        while (pubs < tiles) { if (!service()) { if (timed_out(t0)) break; __nanosleep(20); } }
      }
      __syncwarp();
      asm volatile("barrier.cluster.arrive.relaxed.aligned; barrier.cluster.wait.aligned;" ::: "memory");
    } else {
      const int uq = lane >> 3, j = lane & 3;
      const unsigned wbase = ep0 * (unsigned)(NWTASK + 2 * gridDim.x);
      while (true) {
        int info = -1;
        if (lane == 0) {
          const unsigned task = atomicAdd(&g_wticket, 1u) - wbase;
          if (task < (unsigned)NWTASK) {
            int r = task, gq = 0, fin = 0;
            for (int i = -2;; ) {
              gq = fin ? i : i + 2;
              const int c = (gq >= 0 && gq < NGRP) ? 64 * grp_n(gq) : 0;
              if (r < c) break;
              r -= c;
              if (fin) i++;
              fin ^= 1;
            }
            info = (grp_rb0(gq) * 64 + r) | (fin << 16);
          }
        }
        info = __shfl_sync(~0u, info, 0);
        if (info < 0) break;
        const int r2 = info & 0xffff, fin = info >> 16, r8 = r2 >> 2, rb = r2 >> 6;
        const int cl = (r2 & 3) * 8 + (lane & 7), g = cl >> 2;
        uint4* hp = g_hT + ((size_t)r8 * 18 + uq) * 32 + cl;
        const uint4* p = (fin ? g_p2 : g_p1) + ((size_t)r8 * 18 + uq) * (SPL * 32) + cl;
        const size_t roff = (size_t)(r8 * 8 + g) * (DM / 2) + uq * 16 + j;
        const uint32_t* e = fin ? reinterpret_cast<const uint32_t*>(b2) + uq * 16 + j : reinterpret_cast<const uint32_t*>(x) + roff;
        const bool v4 = uq < 2;
        uint4 hv[5];
#pragma unroll
        for (int t = 0; t < 5; t++) {
          hv[t] = make_uint4(0, 0, 0, 0);
          if (t < 4 || v4) hv[t] = make_uint4(ldg32(e + t * 64), ldg32(e + t * 64 + 4), ldg32(e + t * 64 + 8), ldg32(e + t * 64 + 12));
        }
        if (lane == 0) wait_cnt(fin ? &g_cntP2[rb * PAD] : &g_cntP1[rb * PAD], epoch * 36, 36, t0);
        __syncwarp();
        TR_T(tr0);
        float s = 0.f;
#pragma unroll
        for (int b = 0; b < 2; b++) {
          uint4 v[3][SPL], r[3];
#pragma unroll
          for (int t = 0; t < 3 - b; t++) {
            const int tt = b * 3 + t;
#pragma unroll
            for (int q = 0; q < SPL; q++) { v[t][q] = make_uint4(0, 0, 0, 0); if (tt < 4 || v4) v[t][q] = ldg_cg(p + (tt * 4 * SPL + q) * 32); }
          }
          if (fin) {
#pragma unroll
            for (int t = 0; t < 3 - b; t++) { const int tt = b * 3 + t; r[t] = make_uint4(0, 0, 0, 0); if (tt < 4 || v4) r[t] = ldg_cg(hp + tt * 128); }
          }
#pragma unroll
          for (int t = 0; t < 3 - b; t++) {
            const int tt = b * 3 + t;
            float f[8] = {0.f, 0.f, 0.f, 0.f, 0.f, 0.f, 0.f, 0.f};
#pragma unroll
            for (int q = 0; q < SPL; q++) acc8(f, v[t][q]);
            acc8(f, hv[tt]);
            if (fin) acc8(f, r[t]);
            const uint4 h = make_uint4(pack2(f[0], f[1]), pack2(f[2], f[3]), pack2(f[4], f[5]), pack2(f[6], f[7]));
            hv[tt] = h;
            if (tt < 4 || v4) {
              if (fin) { uint32_t* o = reinterpret_cast<uint32_t*>(out) + roff + tt * 64; o[0] = h.x; o[4] = h.y; o[8] = h.z; o[12] = h.w; }
              else stg128(hp + tt * 128, h.x, h.y, h.z, h.w);
            }
            s += ((bflo(h.x) + bfhi(h.x)) + (bflo(h.y) + bfhi(h.y))) + ((bflo(h.z) + bfhi(h.z)) + (bflo(h.w) + bfhi(h.w)));
          }
        }
        if (!fin) {
          s += __shfl_xor_sync(~0u, s, 1); s += __shfl_xor_sync(~0u, s, 2); s += __shfl_xor_sync(~0u, s, 8); s += __shfl_xor_sync(~0u, s, 16);
          const float mean = s * (1.f / DM);
          float dv[5][8];
          float q = 0.f;
#pragma unroll
          for (int t = 0; t < 5; t++) {
            dv[t][0] = bflo(hv[t].x) - mean; dv[t][1] = bfhi(hv[t].x) - mean; dv[t][2] = bflo(hv[t].y) - mean; dv[t][3] = bfhi(hv[t].y) - mean;
            dv[t][4] = bflo(hv[t].z) - mean; dv[t][5] = bfhi(hv[t].z) - mean; dv[t][6] = bflo(hv[t].w) - mean; dv[t][7] = bfhi(hv[t].w) - mean;
            float qq = 0.f;
#pragma unroll
            for (int i = 0; i < 8; i++) qq = fmaf(dv[t][i], dv[t][i], qq);
            if (t < 4 || v4) q += qq;
          }
          q += __shfl_xor_sync(~0u, q, 1); q += __shfl_xor_sync(~0u, q, 2); q += __shfl_xor_sync(~0u, q, 8); q += __shfl_xor_sync(~0u, q, 16);
          const float rs = rsqrtf(q * (1.f / DM) + 1e-5f);
          uint4* dst = g_hnT + ((size_t)rb * 9 + (uq >> 1)) * 1024 + (r8 & 15) * 64 + ((uq & 1) * 4 + j) * 8 + g;
#pragma unroll
          for (int t = 0; t < 5; t++)
            if (t < 4 || v4)
              stg128(dst + t * 2048, pack2(dv[t][0] * rs, dv[t][1] * rs), pack2(dv[t][2] * rs, dv[t][3] * rs),
                     pack2(dv[t][4] * rs, dv[t][5] * rs), pack2(dv[t][6] * rs, dv[t][7] * rs));
          __syncwarp();
          if (lane == 0) red_release(&g_cntH[rb * PAD]);
        }
        if (lane == 0 && (r2 & 3) == 0) TR_LOG((7 + fin) | ((r8 & 15) << 8) | (rb << 24), tr0, tr0);
      }
      if (lane == 0) {
        if (atomicAdd(&g_done, 1u) == epoch * 2 * gridDim.x - 1) g_epoch = epoch;
      }
      __syncwarp();
      asm volatile("barrier.cluster.arrive.relaxed.aligned; barrier.cluster.wait.aligned;" ::: "memory");
    }
  } else {
    asm volatile("setmaxnreg.inc.sync.aligned.u32 %0;" :: "n"(REG_C));
    const int g = lane >> 2, j = lane & 3;
    const int l0 = __shfl_sync(~0u, lane == 0, lane);
    for (int seq = wg;; seq += 2) {
      mbar_wait(bar + B_D + (seq & 3) * 8, (seq >> 2) & 1, t0);
      uint4 d = lds128(sb + SM_DESC + (seq & 3) * 16);
      d.x = __shfl_sync(~0u, d.x, 0); d.y = __shfl_sync(~0u, d.y, 0); d.z = __shfl_sync(~0u, d.z, 0);
      const int type = d.x & 255;
      const int sl = (d.x >> 8) & 255, kc = (d.x >> 16) & 255, rb = d.x >> 24;
      const int nkb = task_nkb(type, kc);
      const int last = (d.y >> 16) & 1; const bool needb = (d.y >> 17) & 1;
      int st = d.y & 255, ph = ((d.y >> 8) & 1) ^ 1, prev = 0;
      float acc[2][64];
      {
        const uint32_t* bp = reinterpret_cast<const uint32_t*>(b1 + sl * 128) + j;
#pragma unroll
        for (int i = 0; i < 16; i++) {
          uint32_t b = 0;
          if (type == T_F1) b = ldg32(bp + i * 4);
          acc[0][4 * i] = acc[0][4 * i + 2] = acc[1][4 * i] = acc[1][4 * i + 2] = bflo(b);
          acc[0][4 * i + 1] = acc[0][4 * i + 3] = acc[1][4 * i + 1] = acc[1][4 * i + 3] = bfhi(b);
        }
      }
      fence_regs(acc[0]); fence_regs(acc[1]);
      if (seq > 0) bar_sync(3 + wg, 256);
      if (type == T_END) { if (d.y == 0) bar_arrive(3 + (wg ^ 1), 256); break; }
      TR_T(tr0);
      auto mainloop = [&](auto mode) {
        constexpr int MD = decltype(mode)::value;
        constexpr int PER = MD == 2 ? 4 : 3;
        const uint64_t a_hi = make_desc(0, 128, type == T_QA ? 2048 : 1024, 0), b_hi = MD == 2 ? make_desc(0, 4096, 512, 2) : make_desc(0, 8192, 1024, 1);
        const uint32_t a_off = type == T_QA ? 64 : 512;
        bool oka = false;
        int eb = 0, ec = 0;
        for (int kb = 0; kb < nkb; kb++) {
          if (needb) mbar_wait(bar + B_FB + kb * 8, (d.z >> kb) & 1, t0);
          if (!oka) mbar_wait(bar + B_FA + st * 8, ph, t0);
          const uint64_t da = a_hi + ((((sb + SM_A) & 0x3FFFF) >> 4) + st * 1024), db = b_hi + ((((sb + SM_B) & 0x3FFFF) >> 4) + kb * (MD == 2 ? 768 : 1024));
          int nst = st + 1, nph = ph;
          if (nst == NS) { nst = 0; nph ^= 1; }
          wg_fence();
#pragma unroll
          for (int ks = 0; ks < 4; ks++) {
            if (MD == 1) {
              wgmma_n128<1, 0>(acc[0], db + ks * 128, da + ks * 16, 1);
              wgmma_n128<1, 0>(acc[1], db + 512 + ks * 128, da + ks * 16, 1);
            } else if (MD == 0) {
              wgmma_n128<0, 1>(acc[0], da + ks * 16, db + ks * 128, 1);
              wgmma_n128<0, 1>(acc[1], da + a_off + ks * 16, db + ks * 128, 1);
            } else {
              wgmma_n96<0, 1>(acc[0], da + ks * 16, db + ks * 64, 1);
              wgmma_n96<0, 1>(acc[1], da + 512 + ks * 16, db + ks * 64, 1);
            }
            if (ks == 0) {
              wg_commit();
              wg_wait<1>();
              arrive2_if(bar + B_EA + prev * 8, pd, l0 & (kb > 0), 1);
              mbar_arrive_if(bar + B_EB + eb * 8, l0 & (ec == PER) & last);
              if (ec == PER) { ec = 0; eb++; }
              ec++;
              wg_fence();
            }
            if (ks == 2) {
              if (kb == nkb - 1) { oka = false; if (type != T_QA) bar_arrive(3 + (wg ^ 1), 256); }
              else oka = mbar_try(bar + B_FA + nst * 8, nph);
              wg_fence();
            }
          }
          wg_commit();
          prev = st; st = nst; ph = nph;
        }
        wg_wait<0>();
      };
      if (type == T_V) mainloop(IntC<1>()); else if (type == T_OP || type == T_F2) mainloop(IntC<2>()); else mainloop(IntC<0>());
      arrive2_if(bar + B_EA + prev * 8, pd, l0, 1);
      mbar_arrive_if(bar + B_EB + 16, l0 & last);
      fence_regs(acc[0]); fence_regs(acc[1]);
      TR_T(tr1);
      unsigned* cnt;
      if (type <= T_V) {
        uint4* base = type == T_V ? g_Vf + (((size_t)sl * NSEG + rb * 4) * 8 + w) * 64 + lane : g_Kf + ((size_t)sl * 128 + rb * 8 + w) * 256 + lane;
        const int smb = type == T_V ? 256 : 1024, sq2 = type == T_V ? 512 : 64;
#pragma unroll
        for (int mb = 0; mb < 2; mb++) {
#pragma unroll
          for (int q = 0; q < 8; q++) {
            const float* c = &acc[mb][q * 8];
            stg128(base + mb * smb + (q >> 1) * sq2 + (q & 1) * 32, pack2(c[0], c[1]), pack2(c[2], c[3]), pack2(c[4], c[5]), pack2(c[6], c[7]));
          }
        }
        cnt = &g_kvflag[rb * 64 + type * 32 + sl];
      } else if (type == T_OP || type == T_F2) {
        uint4* base = (type == T_OP ? g_p1 : g_p2) + (((size_t)(rb * 16 + w * 2) * 18 + sl * 3) * SPL + kc) * 32 + lane;
#pragma unroll
        for (int u = 0; u < 3; u++)
#pragma unroll
          for (int mb = 0; mb < 2; mb++)
#pragma unroll
            for (int hi = 0; hi < 2; hi++) {
              const float* c = &acc[mb][u * 16 + hi * 2];
              stg128(base + ((mb * 8 + hi) * 18 + u) * (SPL * 32), pack2(c[0], c[1]), pack2(c[4], c[5]), pack2(c[8], c[9]), pack2(c[12], c[13]));
            }
        cnt = type == T_OP ? &g_cntP1[(rb) * PAD] : &g_cntP2[(rb) * PAD];
      } else if (type == T_F1) {
        uint4* base = g_gT + ((size_t)rb * 72 + sl * 2) * 1024 + w * 128 + j * 8 + g;
#pragma unroll
        for (int u = 0; u < 4; u++) {
#pragma unroll
          for (int mb = 0; mb < 2; mb++) {
#pragma unroll
            for (int hi = 0; hi < 2; hi++) {
              uint32_t p[4];
#pragma unroll
              for (int i = 0; i < 4; i++) {
                const float* c = &acc[mb][(u * 4 + i) * 4 + hi * 2];
                p[i] = pack2(gelu_tanh(c[0]), gelu_tanh(c[1]));
              }
              stg128(base + (u >> 1) * 1024 + (mb * 8 + hi) * 64 + (u & 1) * 32, p[0], p[1], p[2], p[3]);
            }
          }
        }
        cnt = &g_cntG[(rb * 8 + sl / 6) * PAD];
      } else {
        uint32_t qa[2][8][4];
#pragma unroll
        for (int mb = 0; mb < 2; mb++)
#pragma unroll
          for (int ks = 0; ks < 8; ks++)
#pragma unroll
            for (int i = 0; i < 4; i++) qa[mb][ks][i] = pack2(acc[mb][ks * 8 + 2 * i], acc[mb][ks * 8 + 2 * i + 1]);
        float sc[2][5][4];
#pragma unroll
        for (int mb = 0; mb < 2; mb++)
#pragma unroll
          for (int n = 0; n < 5; n++) { sc[mb][n][0] = sc[mb][n][1] = sc[mb][n][2] = sc[mb][n][3] = 0.f; }
        auto stg_i = [&](int e) { const int q = st + e; return q >= NS ? q - NS : q; };
        auto stg_p = [&](int e) { return st + e >= NS ? ph ^ 1 : ph; };
        const int ek = w >> 1;
        const uint32_t woff = sb + SM_A + (w & 1) * 8192 + lane * 16;
        {
          mbar_wait(bar + B_FA + stg_i(ek) * 8, stg_p(ek), t0);
          const uint32_t ka = woff + stg_i(ek) * 16384;
          uint4 kf[16];
#pragma unroll
          for (int i = 0; i < 16; i++) kf[i] = lds128(ka + i * 512);
#pragma unroll
          for (int ks = 0; ks < 8; ks++) {
#pragma unroll
            for (int mb = 0; mb < 2; mb++) {
              mma16816(sc[mb][0], qa[mb][ks], kf[ks].x, kf[ks].z);
              mma16816(sc[mb][1], qa[mb][ks], kf[ks].y, kf[ks].w);
              mma16816(sc[mb][2], qa[mb][ks], kf[8 + ks].x, kf[8 + ks].z);
              if (mb == 1) mma16816(sc[mb][3], qa[mb][ks], kf[8 + ks].y, kf[8 + ks].w);
            }
          }
          __syncwarp();
          arrive2_if(bar + B_EA + stg_i(ek) * 8, pd, l0, 2);
        }
        uint4 vf[16], km[4], vm[4];
        TR_T(tq0);
        {
          mbar_wait(bar + B_FA + stg_i(2) * 8, stg_p(2), t0);
          const uint32_t ma = sb + SM_A + stg_i(2) * 16384 + w * 2048 + lane * 16;
#pragma unroll
          for (int i = 0; i < 4; i++) km[i] = lds128(ma + i * 512);
          float s2[2][4] = {{0.f, 0.f, 0.f, 0.f}, {0.f, 0.f, 0.f, 0.f}};
#pragma unroll
          for (int u = 0; u < 4; u++) {
#pragma unroll
            for (int mb = 0; mb < 2; mb++) {
              mma16816(sc[mb][4], qa[mb][2 * u], km[u].x, km[u].y);
              mma16816(s2[mb], qa[mb][2 * u + 1], km[u].z, km[u].w);
            }
          }
#pragma unroll
          for (int mb = 0; mb < 2; mb++)
#pragma unroll
            for (int i = 0; i < 4; i++) sc[mb][4][i] += s2[mb][i];
          const uint32_t z = __float_as_uint(sc[1][4][3]) & (d.w);
          mbar_wait(bar + B_FA + stg_i(3 + ek) * 8, stg_p(3 + ek), t0);
          const uint32_t va = woff + stg_i(3 + ek) * 16384 + z;
#pragma unroll
          for (int i = 0; i < 4; i++) vm[i] = lds128(ma + z + 8192 + i * 512);
#pragma unroll
          for (int i = 0; i < 16; i++) vf[i] = lds128(va + i * 512);
        }
        const float scl = 0.08838834764831845f * 1.4426950408889634f;
        const float NEG = -INFINITY;
        uint32_t pa[2][5][2];
        float inv[2][2];
#pragma unroll
        for (int mb = 0; mb < 2; mb++) {
#pragma unroll
          for (int hi = 0; hi < 2; hi++) {
            const int nd = mb + 2 * hi;
            if (2 * j > g) sc[mb][nd][hi * 2] = NEG;
            if (2 * j + 1 > g) sc[mb][nd][hi * 2 + 1] = NEG;
            float m = fmaxf(sc[mb][4][hi * 2], sc[mb][4][hi * 2 + 1]);
#pragma unroll
            for (int n = 0; n < 4; n++) if (n <= nd) m = fmaxf(m, fmaxf(sc[mb][n][hi * 2], sc[mb][n][hi * 2 + 1]));
            m = fmaxf(m, __shfl_xor_sync(~0u, m, 1)); m = fmaxf(m, __shfl_xor_sync(~0u, m, 2));
            const float mc = m * scl;
            float l = 0.f;
#pragma unroll
            for (int n = 0; n < 5; n++) {
              if (n <= nd || n == 4) {
                const float e0 = ex2(fmaf(sc[mb][n][hi * 2], scl, -mc)), e1 = ex2(fmaf(sc[mb][n][hi * 2 + 1], scl, -mc));
                l += e0 + e1;
                pa[mb][n][hi] = pack2(e0, e1);
              } else pa[mb][n][hi] = 0u;
            }
            l += __shfl_xor_sync(~0u, l, 1); l += __shfl_xor_sync(~0u, l, 2);
            inv[mb][hi] = __fdividef(1.f, l);
          }
        }
        asm volatile("" :: "r"(vm[3].w), "r"(vf[15].w) : "memory");
        __syncwarp();
        arrive2_if(bar + B_EA + stg_i(3 + ek) * 8, pd, l0, 2);
        arrive2_if(bar + B_EA + stg_i(2) * 8, pd, l0, 1);
        TR_T(tq1);
        uint32_t op[4][2][2][4];
        uint4* obase = g_oT + ((size_t)rb * 64 + sl * 2) * 1024 + w * 256 + j * 8 + g;
#pragma unroll
        for (int u = 0; u < 4; u++) {
          float o[2][4][4];
#pragma unroll
          for (int mb = 0; mb < 2; mb++) {
#pragma unroll
            for (int i = 0; i < 4; i++) {
              o[mb][i][0] = o[mb][i][1] = o[mb][i][2] = o[mb][i][3] = 0.f;
              const uint4 v0 = vf[(2 * u + (i >> 1)) * 2], v1 = vf[(2 * u + (i >> 1)) * 2 + 1];
              const uint32_t vmw = i == 0 ? vm[u].x : i == 1 ? vm[u].y : i == 2 ? vm[u].z : vm[u].w;
              mma1688(o[mb][i], pa[mb][4][0], pa[mb][4][1], vmw);
              mma16816(o[mb][i], pa[mb][0][0], pa[mb][0][1], pa[mb][1][0], pa[mb][1][1], (i & 1) ? v0.y : v0.x, (i & 1) ? v0.w : v0.z);
              if (mb == 0) mma1688(o[mb][i], pa[mb][2][0], pa[mb][2][1], (i & 1) ? v1.y : v1.x);
              else mma16816(o[mb][i], pa[mb][2][0], pa[mb][2][1], pa[mb][3][0], pa[mb][3][1], (i & 1) ? v1.y : v1.x, (i & 1) ? v1.w : v1.z);
            }
          }
          if (u == 3) bar_arrive(3 + (wg ^ 1), 256);
#pragma unroll
          for (int mb = 0; mb < 2; mb++) {
#pragma unroll
            for (int hi = 0; hi < 2; hi++) {
              const float s = inv[mb][hi];
#pragma unroll
              for (int i = 0; i < 4; i++) op[u][mb][hi][i] = pack2(o[mb][i][hi * 2] * s, o[mb][i][hi * 2 + 1] * s);
            }
          }
        }
        TR_T(tq2);
#pragma unroll
        for (int u = 0; u < 4; u++)
#pragma unroll
          for (int mb = 0; mb < 2; mb++)
#pragma unroll
            for (int hi = 0; hi < 2; hi++)
              stg128(obase + (u >> 1) * 1024 + (mb + 2 * hi) * 64 + (u & 1) * 32, op[u][mb][hi][0], op[u][mb][hi][1], op[u][mb][hi][2], op[u][mb][hi][3]);
        if (tid == wg * 128) TR_LOG(10 | (rb << 24), tq0 - tr1, tq1 - tr1);
        if (tid == wg * 128) TR_LOG(11 | (rb << 24), tq2 - tr1, tr1);
        cnt = &g_cntO[(rb * 8 + (sl < 12 ? sl / 6 : 2 + (sl - 12) / 5)) * PAD];
      }
      mbar_wait(bar + B_PE + wg * 8, ((seq >> 1) & 1) ^ 1, t0);
      if (w == 0 && l0) {
        sts64(sb + SM_PUB + wg * 8, (uint32_t)(uintptr_t)cnt, (uint32_t)((uintptr_t)cnt >> 32));
        TR_LOG(d.x, tr0, tr1);
      }
      __syncwarp();
      mbar_arrive_if(bar + B_PD + wg * 8, l0);
    }
    __syncwarp();
    asm volatile("barrier.cluster.arrive.relaxed.aligned; barrier.cluster.wait.aligned;" ::: "memory");
  }
}
}
typedef CUresult (*EncodeFn)(CUtensorMap*, CUtensorMapDataType, cuuint32_t, void*, const cuuint64_t*, const cuuint64_t*, const cuuint32_t*,
                             const cuuint32_t*, CUtensorMapInterleave, CUtensorMapSwizzle, CUtensorMapL2promotion, CUtensorMapFloatOOBfill);
static EncodeFn get_encode() {
  void* fn = nullptr; cudaDriverEntryPointQueryResult st;
  cudaGetDriverEntryPoint("cuTensorMapEncodeTiled", &fn, cudaEnableDefault, &st);
  return (EncodeFn)fn;
}
static CUtensorMap map2d(EncodeFn enc, const void* p, int rows, int cols, int brow) {
  CUtensorMap m;
  cuuint64_t dim[2] = {(cuuint64_t)cols, (cuuint64_t)rows}; cuuint64_t str[1] = {(cuuint64_t)cols * 2};
  cuuint32_t box[2] = {64, (cuuint32_t)brow}, es[2] = {1, 1};
  enc(&m, CU_TENSOR_MAP_DATA_TYPE_BFLOAT16, 2, (void*)p, dim, str, box, es, CU_TENSOR_MAP_INTERLEAVE_NONE, CU_TENSOR_MAP_SWIZZLE_128B,
      CU_TENSOR_MAP_L2_PROMOTION_L2_256B, CU_TENSOR_MAP_FLOAT_OOB_FILL_NONE);
  return m;
}
static CUtensorMap map5d(EncodeFn enc, const void* p, int rows, int cols, int bcols) {
  CUtensorMap m;
  const cuuint64_t rs = (cuuint64_t)cols * 2;
  cuuint64_t dim[5] = {(cuuint64_t)cols, 2, 4, 4, (cuuint64_t)rows / 32}; cuuint64_t str[4] = {rs, 8 * rs, 2 * rs, 32 * rs};
  cuuint32_t box[5] = {(cuuint32_t)bcols, 2, 4, 4, 2}, es[5] = {1, 1, 1, 1, 1};
  enc(&m, CU_TENSOR_MAP_DATA_TYPE_BFLOAT16, 5, (void*)p, dim, str, box, es, CU_TENSOR_MAP_INTERLEAVE_NONE,
      bcols == 64 ? CU_TENSOR_MAP_SWIZZLE_128B : CU_TENSOR_MAP_SWIZZLE_64B,
      CU_TENSOR_MAP_L2_PROMOTION_L2_256B, CU_TENSOR_MAP_FLOAT_OOB_FILL_NONE);
  return m;
}
static CUtensorMap map3d(EncodeFn enc, const void* p) {
  CUtensorMap m;
  cuuint64_t dim[3] = {64, (cuuint64_t)DM, HD / 64}; cuuint64_t str[2] = {(cuuint64_t)HD * 2, 128};
  cuuint32_t box[3] = {64, 16, 2}, es[3] = {1, 1, 1};
  enc(&m, CU_TENSOR_MAP_DATA_TYPE_BFLOAT16, 3, (void*)p, dim, str, box, es, CU_TENSOR_MAP_INTERLEAVE_NONE, CU_TENSOR_MAP_SWIZZLE_128B,
      CU_TENSOR_MAP_L2_PROMOTION_L2_256B, CU_TENSOR_MAP_FLOAT_OOB_FILL_NONE);
  return m;
}
template <typename... KArgs, typename... Args>
static void launch(void (*k)(KArgs...), int grid, int block, int smem, cudaStream_t s, int cluster, bool pdl, Args... args) {
  cudaLaunchConfig_t cfg = {};
  cfg.gridDim = dim3(grid); cfg.blockDim = dim3(block); cfg.dynamicSmemBytes = smem; cfg.stream = s;
  cudaLaunchAttribute at[2]; int n = 0;
  if (cluster > 1) { at[n].id = cudaLaunchAttributeClusterDimension; at[n].val.clusterDim.x = cluster; at[n].val.clusterDim.y = 1; at[n].val.clusterDim.z = 1; n++; }
  if (pdl) { at[n].id = cudaLaunchAttributeProgrammaticStreamSerialization; at[n].val.programmaticStreamSerializationAllowed = 1; n++; }
  cfg.attrs = at; cfg.numAttrs = n;
  cudaLaunchKernelEx(&cfg, k, KArgs(args)...);
}
struct Ctx {
  mega::Maps maps;
  chain::Maps cmaps;
  cudaStream_t s2; cudaEvent_t evFork, evJoin;
  bool init;
};
static void setup(Ctx& c, void* const* d_in) {
  EncodeFn enc = get_encode();
  c.maps.m[mega::T_K] = map2d(enc, d_in[3], DM, HD, 64); c.maps.m[mega::T_V] = map2d(enc, d_in[4], DM, HD, 64);
  c.maps.m[mega::T_QA] = map2d(enc, d_in[2], DM, HD, 64);
  c.maps.m[mega::T_OP] = map5d(enc, d_in[5], HD, DM, 32); c.maps.m[mega::T_F1] = map5d(enc, d_in[8], DM, FF, 64); c.maps.m[mega::T_F2] = map5d(enc, d_in[10], FF, DM, 32);
  c.cmaps.q = map3d(enc, d_in[2]); c.cmaps.k = map3d(enc, d_in[3]); c.cmaps.v = map3d(enc, d_in[4]); c.cmaps.o = map2d(enc, d_in[5], HD, DM, 128);
  cudaFuncSetAttribute(chain::chain_kernel, cudaFuncAttributeNonPortableClusterSizeAllowed, 1);
  cudaFuncSetAttribute(chain::chain_kernel, cudaFuncAttributeMaxDynamicSharedMemorySize, chain::SM_TOTAL);
  cudaFuncSetAttribute(mega::mega_kernel, cudaFuncAttributeMaxDynamicSharedMemorySize, mega::SM_TOTAL);
  cudaFuncAttributes fa;
  cudaFuncGetAttributes(&fa, gate_kernel);
  int lo, hi; cudaDeviceGetStreamPriorityRange(&lo, &hi);
  cudaStreamCreateWithPriority(&c.s2, cudaStreamNonBlocking, hi);
  cudaEventCreateWithFlags(&c.evFork, cudaEventDisableTiming); cudaEventCreateWithFlags(&c.evJoin, cudaEventDisableTiming);
  c.init = true;
}
#define NCH 64
static Ctx g_ctx;
extern "C" void kernel_launch(void* const* d_in, const int* in_sizes, int n_in, void* d_out, int out_size) {
  Ctx& c = g_ctx;
  if (!c.init) setup(c, d_in);
  const bf16 *x = (const bf16*)d_in[0], *mem0 = (const bf16*)d_in[1], *b1 = (const bf16*)d_in[9], *b2 = (const bf16*)d_in[11];
  bf16* out = (bf16*)d_out;
  cudaStream_t s = cudaStreamPerThread;
  cudaEventRecord(c.evFork, s);
  cudaStreamWaitEvent(c.s2, c.evFork, 0);
  launch(chain::chain_kernel, NCH, chain::NTHREADS, chain::SM_TOTAL, c.s2, 16, false, c.cmaps, mem0, x, (const bf16*)d_in[2], (const bf16*)d_in[3], (const bf16*)d_in[4], (const bf16*)d_in[5], 0u);
  cudaEventRecord(c.evJoin, c.s2);
  launch(gate_kernel, 1, 1, 0, s, 1, false);
  launch(mega::mega_kernel, 132, 384, mega::SM_TOTAL, s, 2, true, c.maps, x, b1, b2, out);
  cudaStreamWaitEvent(s, c.evJoin, 0);
}
```

```cpp
#include <cuda_runtime.h>
#include <cuda_bf16.h>
#include <cuda.h>
#include <stdint.h>

typedef __nv_bfloat16 bf16;

constexpr int SEQ = 2048, DM = 576, NH = 32, DH = 128, HD = 4096, FF = 4608, NSEG = 64, NRB = 16;

__device__ __align__(1024) uint4 g_Kf[NH * 256 * 4 * 32];
__device__ __align__(1024) uint4 g_Vf[NH * NSEG * 128 * 4];
__device__ __align__(1024) uint4 g_Kmf[NH * NSEG * 4 * 32];
__device__ __align__(1024) uint4 g_Vmf[NH * NSEG * 4 * 32];
__device__ __align__(8192) uint4 g_xch[64 * 512];
__device__ unsigned g_kvflag[NRB * 64];
__device__ unsigned g_memflag[NH * 8];
__device__ __align__(1024) uint4 g_xnT[NRB * 9 * 1024];
__device__ unsigned g_cntX[NRB * 32];
__device__ unsigned g_epoch;
__device__ unsigned g_resident;
__device__ unsigned g_err;

__device__ __forceinline__ uint32_t smem_u32(const void* p) { return (uint32_t)__cvta_generic_to_shared(p); }
__device__ __forceinline__ void mbar_init(uint32_t a, int cnt) { asm volatile("mbarrier.init.shared::cta.b64 [%0], %1;" :: "r"(a), "r"(cnt) : "memory"); }
__device__ __forceinline__ void mbar_expect(uint32_t a, int bytes) { asm volatile("mbarrier.arrive.expect_tx.shared::cta.b64 _, [%0], %1;" :: "r"(a), "r"(bytes) : "memory"); }
__device__ __forceinline__ void mbar_arrive(uint32_t a) { asm volatile("mbarrier.arrive.shared::cta.b64 _, [%0];" :: "r"(a) : "memory"); }
__device__ __forceinline__ void mbar_arrive_if(uint32_t a, int p) { asm volatile("{ .reg .pred q; setp.ne.b32 q, %1, 0; @q mbarrier.arrive.shared::cta.b64 _, [%0]; }" :: "r"(a), "r"(p) : "memory"); }
__device__ __forceinline__ bool mbar_try(uint32_t a, uint32_t parity) {
  uint32_t ok;
  asm volatile("{ .reg .pred p; mbarrier.try_wait.parity.shared::cta.b64 p, [%1], %2; selp.u32 %0, 1, 0, p; }" : "=r"(ok) : "r"(a), "r"(parity) : "memory");
  return ok;
}
__device__ __forceinline__ bool mbar_test(uint32_t a, uint32_t parity) {
  uint32_t ok;
  asm volatile("{ .reg .pred p; mbarrier.test_wait.parity.shared::cta.b64 p, [%1], %2; selp.u32 %0, 1, 0, p; }" : "=r"(ok) : "r"(a), "r"(parity) : "memory");
  return ok;
}
__device__ __forceinline__ bool mbar_try_cl(uint32_t a, uint32_t parity) {
  uint32_t ok;
  asm volatile("{ .reg .pred p; mbarrier.try_wait.parity.acquire.cluster.shared::cta.b64 p, [%1], %2; selp.u32 %0, 1, 0, p; }" : "=r"(ok) : "r"(a), "r"(parity) : "memory");
  return ok;
}
__device__ __forceinline__ uint32_t clk32() { uint32_t c; asm volatile("mov.u32 %0, %%clock;" : "=r"(c)); return c; }
constexpr uint32_t TIMEOUT_CLKS = 400000000u;
__device__ __forceinline__ bool timed_out(uint32_t t0) {
  if (clk32() - t0 > TIMEOUT_CLKS) { g_err = 1; return true; }
  return false;
}
__device__ __forceinline__ void mbar_wait(uint32_t a, uint32_t parity, uint32_t t0) {
  while (!mbar_try(a, parity)) { if (timed_out(t0)) break; }
}
__device__ __forceinline__ void mbar_wait_cl(uint32_t a, uint32_t parity, uint32_t t0) {
  while (!mbar_try_cl(a, parity)) { if (timed_out(t0)) break; }
}
__device__ __forceinline__ uint32_t mapa(uint32_t a, uint32_t r) { uint32_t d; asm volatile("mapa.shared::cluster.u32 %0, %1, %2;" : "=r"(d) : "r"(a), "r"(r)); return d; }
__device__ __forceinline__ void st_async16(uint32_t a, uint32_t x, uint32_t y, uint32_t z, uint32_t w, uint32_t bar) {
  asm volatile("st.async.shared::cluster.mbarrier::complete_tx::bytes.v4.b32 [%0], {%1,%2,%3,%4}, [%5];" :: "r"(a), "r"(x), "r"(y), "r"(z), "r"(w), "r"(bar) : "memory");
}
__device__ __forceinline__ void st_async8(uint32_t a, uint32_t x, uint32_t y, uint32_t bar) {
  asm volatile("st.async.shared::cluster.mbarrier::complete_tx::bytes.v2.b32 [%0], {%1,%2}, [%3];" :: "r"(a), "r"(x), "r"(y), "r"(bar) : "memory");
}
__device__ __forceinline__ void bar_sync(int id, int n) { asm volatile("bar.sync %0, %1;" :: "r"(id), "r"(n) : "memory"); }
__device__ __forceinline__ void bar_arrive(int id, int n) { asm volatile("bar.arrive %0, %1;" :: "r"(id), "r"(n) : "memory"); }
__device__ __forceinline__ void cluster_sync() { asm volatile("barrier.cluster.arrive.release.aligned; barrier.cluster.wait.acquire.aligned;" ::: "memory"); }
__device__ __forceinline__ uint32_t pack2(float lo, float hi) { uint32_t d; asm("cvt.rn.bf16x2.f32 %0, %1, %2;" : "=r"(d) : "f"(hi), "f"(lo)); return d; }
__device__ __forceinline__ float bflo(uint32_t v) { return __uint_as_float(v << 16); }
__device__ __forceinline__ float bfhi(uint32_t v) { return __uint_as_float(v & 0xffff0000u); }
__device__ __forceinline__ uint32_t movmat(uint32_t a) { uint32_t d; asm volatile("movmatrix.sync.aligned.m8n8.trans.b16 %0, %1;" : "=r"(d) : "r"(a)); return d; }
__device__ __forceinline__ uint32_t hadd2bf(uint32_t a, uint32_t b) { uint32_t d; asm("add.rn.bf16x2 %0, %1, %2;" : "=r"(d) : "r"(a), "r"(b)); return d; }
__device__ __forceinline__ void mma16816(float (&c)[4], uint32_t a0, uint32_t a1, uint32_t a2, uint32_t a3, uint32_t b0, uint32_t b1) {
  asm volatile("mma.sync.aligned.m16n8k16.row.col.f32.bf16.bf16.f32 {%0,%1,%2,%3}, {%4,%5,%6,%7}, {%8,%9}, {%0,%1,%2,%3};"
    : "+f"(c[0]), "+f"(c[1]), "+f"(c[2]), "+f"(c[3]) : "r"(a0), "r"(a1), "r"(a2), "r"(a3), "r"(b0), "r"(b1));
}
__device__ __forceinline__ void mma16816(float (&c)[4], const uint32_t (&a)[4], uint32_t b0, uint32_t b1) { mma16816(c, a[0], a[1], a[2], a[3], b0, b1); }
__device__ __forceinline__ void mma1688(float (&c)[4], uint32_t a0, uint32_t a1, uint32_t b0) {
  asm volatile("mma.sync.aligned.m16n8k8.row.col.f32.bf16.bf16.f32 {%0,%1,%2,%3}, {%4,%5}, {%6}, {%0,%1,%2,%3};"
    : "+f"(c[0]), "+f"(c[1]), "+f"(c[2]), "+f"(c[3]) : "r"(a0), "r"(a1), "r"(b0));
}
__device__ __forceinline__ void ldsm4t(uint32_t (&r)[4], uint32_t a) {
  asm volatile("ldmatrix.sync.aligned.m8n8.x4.trans.shared.b16 {%0,%1,%2,%3}, [%4];" : "=r"(r[0]), "=r"(r[1]), "=r"(r[2]), "=r"(r[3]) : "r"(a) : "memory");
}
__device__ __forceinline__ uint4 lds128(uint32_t a) { uint4 v; asm volatile("ld.shared.v4.b32 {%0,%1,%2,%3}, [%4];" : "=r"(v.x), "=r"(v.y), "=r"(v.z), "=r"(v.w) : "r"(a) : "memory"); return v; }
__device__ __forceinline__ uint2 lds64(uint32_t a) { uint2 v; asm volatile("ld.shared.v2.b32 {%0,%1}, [%2];" : "=r"(v.x), "=r"(v.y) : "r"(a) : "memory"); return v; }
__device__ __forceinline__ void sts128(uint32_t a, uint32_t x, uint32_t y, uint32_t z, uint32_t w) { asm volatile("st.shared.v4.b32 [%0], {%1,%2,%3,%4};" :: "r"(a), "r"(x), "r"(y), "r"(z), "r"(w) : "memory"); }
__device__ __forceinline__ void sts64(uint32_t a, uint32_t x, uint32_t y) { asm volatile("st.shared.v2.b32 [%0], {%1,%2};" :: "r"(a), "r"(x), "r"(y) : "memory"); }
__device__ __forceinline__ void sts32(uint32_t a, uint32_t x) { asm volatile("st.shared.b32 [%0], %1;" :: "r"(a), "r"(x) : "memory"); }
__device__ __forceinline__ void cp_async16(uint32_t dst, const void* src) { asm volatile("cp.async.cg.shared.global [%0], [%1], 16;" :: "r"(dst), "l"(src) : "memory"); }
__device__ __forceinline__ void cp_async_wait_all() { asm volatile("cp.async.wait_all;" ::: "memory"); }
__device__ __forceinline__ uint4 ldg_cg(const void* p) { uint4 v; asm volatile("ld.global.cg.v4.b32 {%0,%1,%2,%3}, [%4];" : "=r"(v.x), "=r"(v.y), "=r"(v.z), "=r"(v.w) : "l"(p) : "memory"); return v; }
__device__ __forceinline__ uint4 ld_relaxed16(const void* p) { uint4 v; asm volatile("ld.relaxed.gpu.global.v4.b32 {%0,%1,%2,%3}, [%4];" : "=r"(v.x), "=r"(v.y), "=r"(v.z), "=r"(v.w) : "l"(p) : "memory"); return v; }
__device__ __forceinline__ void st_relaxed16(void* p, uint32_t x, uint32_t y, uint32_t z, uint32_t w) { asm volatile("st.relaxed.gpu.global.v4.b32 [%0], {%1,%2,%3,%4};" :: "l"(p), "r"(x), "r"(y), "r"(z), "r"(w) : "memory"); }
__device__ __forceinline__ unsigned ld_acquire(const unsigned* p) { unsigned v; asm volatile("ld.acquire.gpu.global.u32 %0, [%1];" : "=r"(v) : "l"(p) : "memory"); return v; }
__device__ __forceinline__ uint32_t ldg32(const void* p) { uint32_t v; asm volatile("ld.global.nc.b32 %0, [%1];" : "=r"(v) : "l"(p)); return v; }
__device__ __forceinline__ unsigned ld_relaxed(const unsigned* p) { unsigned v; asm volatile("ld.relaxed.gpu.global.u32 %0, [%1];" : "=r"(v) : "l"(p) : "memory"); return v; }
__device__ __forceinline__ void st_release(unsigned* p, unsigned v) { asm volatile("st.release.gpu.global.u32 [%0], %1;" :: "l"(p), "r"(v) : "memory"); }
__device__ __forceinline__ float ex2(float x) { float y; asm("ex2.approx.ftz.f32 %0, %1;" : "=f"(y) : "f"(x)); return y; }

__device__ __forceinline__ void st_b128(void* p, uint32_t x, uint32_t y, uint32_t z, uint32_t w) {
  asm volatile("{ .reg .b128 t; .reg .b64 lo, hi; mov.b64 lo, {%1,%2}; mov.b64 hi, {%3,%4}; mov.b128 t, {lo,hi}; st.relaxed.gpu.global.b128 [%0], t; }"
    :: "l"(p), "r"(x), "r"(y), "r"(z), "r"(w) : "memory");
}
__device__ __forceinline__ uint4 ld_b128(const void* p) {
  uint4 v;
  asm volatile("{ .reg .b128 t; .reg .b64 lo, hi; ld.relaxed.gpu.global.b128 t, [%4]; mov.b128 {lo,hi}, t; mov.b64 {%0,%1}, lo; mov.b64 {%2,%3}, hi; }"
    : "=r"(v.x), "=r"(v.y), "=r"(v.z), "=r"(v.w) : "l"(p) : "memory");
  return v;
}
__device__ __forceinline__ void wg_fence() { asm volatile("wgmma.fence.sync.aligned;" ::: "memory"); }
__device__ __forceinline__ void wg_commit() { asm volatile("wgmma.commit_group.sync.aligned;" ::: "memory"); }
template <int N> __device__ __forceinline__ void wg_wait() { asm volatile("wgmma.wait_group.sync.aligned %0;" :: "n"(N) : "memory"); }
__device__ __forceinline__ uint64_t make_desc(uint32_t addr, uint32_t lbo, uint32_t sbo, uint32_t mode) {
  return (uint64_t)((addr & 0x3FFFF) >> 4) | ((uint64_t)(lbo >> 4) << 16) | ((uint64_t)(sbo >> 4) << 32) | ((uint64_t)mode << 62);
}
__device__ __forceinline__ void tma2d(uint32_t dst, const CUtensorMap* m, int c0, int c1, uint32_t bar) {
  asm volatile("cp.async.bulk.tensor.2d.shared::cluster.global.mbarrier::complete_tx::bytes [%0], [%1, {%3, %4}], [%2];"
    :: "r"(dst), "l"(m), "r"(bar), "r"(c0), "r"(c1) : "memory");
}
__device__ __forceinline__ void tma5d(uint32_t dst, const CUtensorMap* m, int c0, int c4, uint32_t bar) {
  asm volatile("cp.async.bulk.tensor.5d.shared::cluster.global.mbarrier::complete_tx::bytes [%0], [%1, {%3, %5, %5, %5, %4}], [%2];"
    :: "r"(dst), "l"(m), "r"(bar), "r"(c0), "r"(c4), "r"(0) : "memory");
}
__device__ __forceinline__ void bulk_g2s(uint32_t dst, const void* src, uint32_t bytes, uint32_t bar) {
  asm volatile("cp.async.bulk.shared::cluster.global.mbarrier::complete_tx::bytes [%0], [%1], %2, [%3];" :: "r"(dst), "l"(src), "r"(bytes), "r"(bar) : "memory");
}
__device__ __forceinline__ void stg128(void* p, uint32_t x, uint32_t y, uint32_t z, uint32_t w) {
  asm volatile("st.global.v4.b32 [%0], {%1,%2,%3,%4};" :: "l"(p), "r"(x), "r"(y), "r"(z), "r"(w) : "memory");
}
template <int N> __device__ __forceinline__ void fence_regs(float (&d)[N]) {
#pragma unroll
  for (int i = 0; i < N; i++) asm volatile("" : "+f"(d[i]) :: "memory");
}

#define TR_T(v)
#define TR_VAR(v)
#define TR_SET(v)
#define TR_LOG(info, a, b)
template <int TA, int TB>
__device__ __forceinline__ void wgmma_n96(float (&d)[64], uint64_t da, uint64_t db, int scale_d) {
  asm volatile("{ .reg .pred p; setp.ne.b32 p, %50, 0;\n"
    "wgmma.mma_async.sync.aligned.m64n96k16.f32.bf16.bf16 {%0, %1, %2, %3, %4, %5, %6, %7, %8, %9, %10, %11, %12, %13, %14, %15, %16, %17, %18, %19, %20, %21, %22, %23, %24, %25, %26, %27, %28, %29, %30, %31, %32, %33, %34, %35, %36, %37, %38, %39, %40, %41, %42, %43, %44, %45, %46, %47}, %48, %49, p, 1, 1, %51, %52; }"
    : "+f"(d[0]), "+f"(d[1]), "+f"(d[2]), "+f"(d[3]), "+f"(d[4]), "+f"(d[5]), "+f"(d[6]), "+f"(d[7]), "+f"(d[8]), "+f"(d[9]), "+f"(d[10]), "+f"(d[11]), "+f"(d[12]), "+f"(d[13]), "+f"(d[14]), "+f"(d[15]), "+f"(d[16]), "+f"(d[17]), "+f"(d[18]), "+f"(d[19]), "+f"(d[20]), "+f"(d[21]), "+f"(d[22]), "+f"(d[23]), "+f"(d[24]), "+f"(d[25]), "+f"(d[26]), "+f"(d[27]), "+f"(d[28]), "+f"(d[29]), "+f"(d[30]), "+f"(d[31]), "+f"(d[32]), "+f"(d[33]), "+f"(d[34]), "+f"(d[35]), "+f"(d[36]), "+f"(d[37]), "+f"(d[38]), "+f"(d[39]), "+f"(d[40]), "+f"(d[41]), "+f"(d[42]), "+f"(d[43]), "+f"(d[44]), "+f"(d[45]), "+f"(d[46]), "+f"(d[47])
    : "l"(da), "l"(db), "r"(scale_d), "n"(TA), "n"(TB));
}
template <int TA, int TB>
__device__ __forceinline__ void wgmma_n128(float (&d)[64], uint64_t da, uint64_t db, int scale_d) {
  asm volatile("{ .reg .pred p; setp.ne.b32 p, %66, 0;\n"
    "wgmma.mma_async.sync.aligned.m64n128k16.f32.bf16.bf16 {%0, %1, %2, %3, %4, %5, %6, %7, %8, %9, %10, %11, %12, %13, %14, %15, %16, %17, %18, %19, %20, %21, %22, %23, %24, %25, %26, %27, %28, %29, %30, %31, %32, %33, %34, %35, %36, %37, %38, %39, %40, %41, %42, %43, %44, %45, %46, %47, %48, %49, %50, %51, %52, %53, %54, %55, %56, %57, %58, %59, %60, %61, %62, %63}, %64, %65, p, 1, 1, %67, %68; }"
    : "+f"(d[0]), "+f"(d[1]), "+f"(d[2]), "+f"(d[3]), "+f"(d[4]), "+f"(d[5]), "+f"(d[6]), "+f"(d[7]), "+f"(d[8]), "+f"(d[9]), "+f"(d[10]), "+f"(d[11]), "+f"(d[12]), "+f"(d[13]), "+f"(d[14]), "+f"(d[15]), "+f"(d[16]), "+f"(d[17]), "+f"(d[18]), "+f"(d[19]), "+f"(d[20]), "+f"(d[21]), "+f"(d[22]), "+f"(d[23]), "+f"(d[24]), "+f"(d[25]), "+f"(d[26]), "+f"(d[27]), "+f"(d[28]), "+f"(d[29]), "+f"(d[30]), "+f"(d[31]), "+f"(d[32]), "+f"(d[33]), "+f"(d[34]), "+f"(d[35]), "+f"(d[36]), "+f"(d[37]), "+f"(d[38]), "+f"(d[39]), "+f"(d[40]), "+f"(d[41]), "+f"(d[42]), "+f"(d[43]), "+f"(d[44]), "+f"(d[45]), "+f"(d[46]), "+f"(d[47]), "+f"(d[48]), "+f"(d[49]), "+f"(d[50]), "+f"(d[51]), "+f"(d[52]), "+f"(d[53]), "+f"(d[54]), "+f"(d[55]), "+f"(d[56]), "+f"(d[57]), "+f"(d[58]), "+f"(d[59]), "+f"(d[60]), "+f"(d[61]), "+f"(d[62]), "+f"(d[63])
    : "l"(da), "l"(db), "r"(scale_d), "n"(TA), "n"(TB));
}
#define POLL_MODE 1
#define STAGGER 0
#define WEARLY 6
#define WLATE 1
#define PREF 2
#define CREG 216
#define AREG 72
#define KEEPALIVE 150
#define POLL_REP 2
namespace chain {
constexpr int SLOT = 4096;
constexpr int NX = 8;
constexpr int NPV = 9;
constexpr int NV2 = 18 - NPV;
constexpr int NPERM = 2 * (18 - NX) + NPV;
constexpr int SM_X = 0;
constexpr int SM_V2 = SM_X + 2 * NX * SLOT;
constexpr int SM_KX = SM_V2 + NV2 * SLOT;
constexpr int SM_VX = SM_KX + 8192;
constexpr int SM_WO = SM_VX + 8192;
static_assert(SM_WO == NPERM * SLOT, "staging area = X + V2 + KX + VX");
constexpr int SM_MEM = SM_WO + 5 * 16384;
constexpr int SM_OQK = SM_MEM + 9 * 512;
constexpr int SM_XQK = SM_OQK + 4096;
constexpr int SM_OV = SM_XQK + 4096;
constexpr int SM_XV = SM_OV + 2048;
constexpr int SM_S = SM_XV + 2048;
constexpr int SM_O = SM_S + 1536;
constexpr int SM_RS = SM_O + 2048;
constexpr int SM_MB = SM_RS + 8 * 576;
constexpr int SM_INV = SM_MB + 3 * 1152;
constexpr int SM_BAR = SM_INV + 128;
constexpr int SM_PROF = SM_BAR + 128;
constexpr int SM_TOTAL = SM_PROF + 256;
static_assert(SM_TOTAL <= 232448, "smem");
constexpr int B_AG = 0  , B_XQK = 40, B_XV = 48, B_RS = 56, B_KV = 64, B_L = 72, B_W = 80  ;
constexpr int RS_BYTES = 7 * 512 + 8 * 64;
constexpr int BAR_OQK = 1, BAR_S = 2, BAR_O = 3, BAR_ALL = 4, BAR_L = 5, BAR_AB = 6, BAR_AB2 = 7, BAR_C = 8;
constexpr int NTHREADS = 384;
constexpr int REG_C = CREG, REG_A = AREG;
static_assert(2 * REG_C + REG_A <= 504, "register pool");

#define PROF(slot) do {} while (0)
#define PROFN(slot) do {} while (0)
#define PROFS() do {} while (0)
#define PROF0(slot) do {} while (0)
#define PROF1(slot) do {} while (0)

struct Maps { CUtensorMap q, k, v, o; };
__device__ int g_side[133];
__device__ unsigned g_elect;

__device__ __forceinline__ void mmaq(float (&c)[4], const uint4& a, uint32_t b0, uint32_t b1) { mma16816(c, a.x, a.y, a.z, a.w, b0, b1); }
__device__ __forceinline__ int opaque(int v) { int d; asm volatile("mov.u32 %0, %1;" : "=r"(d) : "r"(v)); return d; }
__device__ __forceinline__ uint32_t dep(uint32_t base, uint32_t v, uint32_t zero) {
  uint32_t d; asm("lop3.b32 %0, %1, %2, %3, 0xF8;" : "=r"(d) : "r"(base), "r"(v), "r"(zero)); return d;
}
__device__ __forceinline__ void tma3d(uint32_t dst, const CUtensorMap* m, int c1, int c2, uint32_t bar) {
  asm volatile("cp.async.bulk.tensor.3d.shared::cluster.global.mbarrier::complete_tx::bytes [%0], [%1, {%5, %3, %4}], [%2];"
    :: "r"(dst), "l"(m), "r"(bar), "r"(c1), "r"(c2), "r"(0) : "memory");
}
__device__ __forceinline__ void tma3d_prefetch(const CUtensorMap* m, int c1, int c2) {
  asm volatile("cp.async.bulk.prefetch.tensor.3d.L2.global [%0, {%3, %1, %2}];" :: "l"(m), "r"(c1), "r"(c2), "r"(0) : "memory");
}
__device__ __forceinline__ uint32_t frag_off(int lane, int cp) {
  const int mat = lane >> 3, r = lane & 7;
  return ((mat >> 1) * 8 + r) * 128 + (((cp * 2 + (mat & 1)) ^ r) * 16);
}

template <bool EXTRA>
__device__ __forceinline__ void softmax_pv(int s, int x, uint32_t sb, uint32_t sl, uint32_t bar, int lane_in, int a, int head, uint32_t t0,
                                           uint32_t (&WX)[8][4], int P) {
  const int lane = opaque(lane_in);
  uint4* const vm_ptr = g_Vmf + (size_t)head * NSEG * 128 + x * 32 + lane;
  const float sc = 0.08838834764831845f * 1.4426950408889634f;
  uint4 vx[4];
#pragma unroll
  for (int u = 0; u < 4; u++) vx[u] = lds128(sl + SM_VX + x * 2048 + u * 512);
  bar_sync(BAR_S, 128);
  const uint4 s0 = lds128(sl + SM_S), s1 = lds128(sl + SM_S + 512), s2 = lds128(sl + SM_S + 1024);
  const bool okv = mbar_try(bar + B_XV, s & 1);
  const uint32_t lv = sb + x * 512 + lane * 8;
  float y[10] = {__uint_as_float(s0.x), __uint_as_float(s0.y), __uint_as_float(s0.z), __uint_as_float(s0.w),
                 __uint_as_float(s1.x), __uint_as_float(s1.y), __uint_as_float(s1.z), __uint_as_float(s1.w),
                 __uint_as_float(s2.x) + __uint_as_float(s2.z), __uint_as_float(s2.y) + __uint_as_float(s2.w)};
  float m = fmaxf(fmaxf(fmaxf(y[0], y[1]), fmaxf(y[2], y[3])), fmaxf(fmaxf(y[4], y[5]), fmaxf(y[6], y[7])));
  m = fmaxf(m, fmaxf(y[8], y[9]));
  if (P) PROF(12);
  m = fmaxf(m, __shfl_xor_sync(0xffffffffu, m, 1));
  m = fmaxf(m, __shfl_xor_sync(0xffffffffu, m, 2));
  if (!okv) mbar_wait(bar + B_XV, s & 1, t0);
  const uint2 ov0 = lds64(lv + SM_OV), xv0 = lds64(lv + SM_XV), ov1 = lds64(lv + SM_OV + 256), xv1 = lds64(lv + SM_XV + 256);
  const float mc = m * sc;
#pragma unroll
  for (int i = 0; i < 10; i++) y[i] = ex2(fmaf(y[i], sc, -mc));
  const uint32_t p0 = pack2(y[0], y[1]), p1 = pack2(y[2], y[3]), p2 = pack2(y[4], y[5]), p3 = pack2(y[6], y[7]), p4 = pack2(y[8], y[9]);
  const uint4 vm = make_uint4(hadd2bf(ov0.x, xv0.x), hadd2bf(ov0.y, xv0.y), hadd2bf(ov1.x, xv1.x), hadd2bf(ov1.y, xv1.y));
  float o0[4] = {0.f, 0.f, 0.f, 0.f}, o1[4] = {0.f, 0.f, 0.f, 0.f}, o2[4] = {0.f, 0.f, 0.f, 0.f}, o3[4] = {0.f, 0.f, 0.f, 0.f};
  mmaq(o0, vx[0], p0, p1); mmaq(o2, vx[2], p0, p1);
  mmaq(o0, vx[1], p2, p3); mmaq(o2, vx[3], p2, p3);
  mma1688(o1, vm.x, vm.y, p4); mma1688(o3, vm.z, vm.w, p4);
  asm volatile("stmatrix.sync.aligned.m8n8.x4.shared.b16 [%0], {%1,%2,%3,%4};" :: "r"(sl + SM_O + x * 512),
    "r"(pack2(o0[0] + o1[0], o0[1] + o1[1])), "r"(pack2(o0[2] + o1[2], o0[3] + o1[3])),
    "r"(pack2(o2[0] + o3[0], o2[1] + o3[1])), "r"(pack2(o2[2] + o3[2], o2[3] + o3[3])) : "memory");
  if (P) PROF(13);
  bar_arrive(BAR_O, NTHREADS);
  if (EXTRA) {
    const uint32_t wa = sb + SM_WO + 4 * 16384 + frag_off(lane, x);
#pragma unroll
    for (int u = 0; u < 8; u++) ldsm4t(WX[u], wa + u * 2048);
    bar_sync(BAR_AB2, 128);
  } else {
    bar_arrive(BAR_AB2, 128);
    if (x == 3) {
      float l = ((y[0] + y[1]) + (y[2] + y[3])) + ((y[4] + y[5]) + (y[6] + y[7])) + (y[8] + y[9]);
      l += __shfl_xor_sync(0xffffffffu, l, 1);
      l += __shfl_xor_sync(0xffffffffu, l, 2);
      float inv; asm("rcp.approx.ftz.f32 %0, %1;" : "=f"(inv) : "f"(l));
      if ((lane & 3) == 0) sts32(sb + SM_INV + lane, __float_as_uint(inv));
      __syncwarp();
      mbar_arrive_if(bar + B_L, lane == 0 && s >= 0);
    }
  }
  if (a == 0 && s >= 0) vm_ptr[(size_t)s * 128] = vm;
}

__device__ __forceinline__ void reduce_exchange(int x, int gi, int a, int s, uint32_t sb, uint32_t bar, int lane_in, uint32_t t0, int P, int bid) {
  const int lane = opaque(lane_in);
  const int tt = x * 32 + lane;
  const bool act = tt < 72;
  const int hc = lane & 1;
  const uint32_t rs_addr = sb + SM_RS + tt * 8;
  const uint32_t mem_addr = sb + SM_MEM + (x < 2 ? (tt >> 1) * 16 : 8 * 512 + (4 * gi + (lane >> 1)) * 16);
  const uint32_t mem_step = x < 2 ? 512 : 0;
  const uint32_t ma = mem_addr + (1 + hc) * mem_step;
  const uint32_t r0 = 2 * ((gi - 1 - hc) & 7) + a, r1 = 2 * ((gi - 3 - hc) & 7) + a, r2 = 2 * ((gi - 5 - hc) & 7) + a, r3 = 2 * ((gi - 7) & 7) + a;
  const uint32_t d0 = mapa(ma, r0), e0 = mapa(bar + B_AG + (x < 2 ? 8 : 32), r0);
  const uint32_t d1 = mapa(ma + 2 * mem_step, r1), e1_ = mapa(bar + B_AG + (x < 2 ? 16 : 32), r1);
  const uint32_t d2 = mapa(ma + 4 * mem_step, r2), e2_ = mapa(bar + B_AG + (x < 2 ? 24 : 32), r2);
  const uint32_t d3 = mapa(ma + 6 * mem_step, r3), e3_ = mapa(bar + B_AG + 32, r3);
  char* const xb = reinterpret_cast<char*>(g_xch) + (tt * 16 + (s & 1) * 2048);
  void* const xw = xb + (size_t)bid * 8192;
  const void* const xr1 = xb + (size_t)(bid ^ 16) * 8192;
  const void* const xr2 = xb + (size_t)(bid ^ 32) * 8192;
  const void* const xr3 = xb + (size_t)(bid ^ 48) * 8192;
  const uint32_t tag = (s + 1) & 15;
  mbar_wait(bar + B_RS, s & 1, t0);
  if (P) PROF(20);
  uint32_t w0 = 0, w1 = 0;
  if (act) {
    uint2 r[8];
#pragma unroll
    for (int u = 0; u < 8; u++) r[u] = lds64(rs_addr + u * 576);
    float f0 = ((bflo(r[0].x) + bflo(r[1].x)) + (bflo(r[2].x) + bflo(r[3].x))) + ((bflo(r[4].x) + bflo(r[5].x)) + (bflo(r[6].x) + bflo(r[7].x)));
    float f1 = ((bfhi(r[0].x) + bfhi(r[1].x)) + (bfhi(r[2].x) + bfhi(r[3].x))) + ((bfhi(r[4].x) + bfhi(r[5].x)) + (bfhi(r[6].x) + bfhi(r[7].x)));
    float f2 = ((bflo(r[0].y) + bflo(r[1].y)) + (bflo(r[2].y) + bflo(r[3].y))) + ((bflo(r[4].y) + bflo(r[5].y)) + (bflo(r[6].y) + bflo(r[7].y)));
    float f3 = ((bfhi(r[0].y) + bfhi(r[1].y)) + (bfhi(r[2].y) + bfhi(r[3].y))) + ((bfhi(r[4].y) + bfhi(r[5].y)) + (bfhi(r[6].y) + bfhi(r[7].y)));
    const uint32_t m0 = (__float_as_uint(f0) & ~15u) | tag;
    if (s >= 0) st_b128(xw, m0, __float_as_uint(f1), __float_as_uint(f2), __float_as_uint(f3));
    if (P) PROF(21);
    uint4 e1, e2, e3;
    const uint32_t mb = sb + SM_MB + tt * 16;
    while (true) {
      cp_async16(mb, xr1); cp_async16(mb + 1152, xr2); cp_async16(mb + 2304, xr3);
      bool ok = false;
#pragma unroll
      for (int i = 0; i < POLL_REP; i++) {
        e1 = lds128(mb); e2 = lds128(mb + 1152); e3 = lds128(mb + 2304);
        ok = (((e1.x ^ tag) | (e2.x ^ tag) | (e3.x ^ tag)) & 15u) == 0;
        if (ok) break;
      }
      if (ok || s < 0 || timed_out(t0)) break;
    }
    if (P) PROF(22);
    f0 = (__uint_as_float(m0) + __uint_as_float(e1.x)) + (__uint_as_float(e2.x) + __uint_as_float(e3.x));
    f1 = (f1 + __uint_as_float(e1.y)) + (__uint_as_float(e2.y) + __uint_as_float(e3.y));
    f2 = (f2 + __uint_as_float(e1.z)) + (__uint_as_float(e2.z) + __uint_as_float(e3.z));
    f3 = (f3 + __uint_as_float(e1.w)) + (__uint_as_float(e2.w) + __uint_as_float(e3.w));
    w0 = pack2(f0, f1); w1 = pack2(f2, f3);
    if (s >= 0) sts64(mem_addr + hc * 8, w0, w1);
  }
  __syncwarp();
  const uint32_t n0 = __shfl_xor_sync(0xffffffffu, w0, 1), n1 = __shfl_xor_sync(0xffffffffu, w1, 1);
  mbar_arrive_if(bar + B_AG + (x == 2 ? 32 : 0), lane == 0);
  if (act && s >= 0) {
    const uint32_t y0 = hc ? n0 : w0, y1 = hc ? n1 : w1, y2 = hc ? w0 : n0, y3 = hc ? w1 : n1;
    st_async16(d0, y0, y1, y2, y3, e0);
    st_async16(d1, y0, y1, y2, y3, e1_);
    st_async16(d2, y0, y1, y2, y3, e2_);
    if (!hc) st_async16(d3, y0, y1, y2, y3, e3_);
  }
  __syncwarp();
  if (P) PROF(23);
}

__global__ void __launch_bounds__(NTHREADS, 1)
chain_kernel(const __grid_constant__ Maps maps, const bf16* __restrict__ mem0, const bf16* x_in, const bf16* Wq, const bf16* Wk, const bf16* Wv,
             const bf16* Wo, uint32_t zero) {
  extern __shared__ __align__(1024) unsigned char smem_raw[];
  const uint32_t sb = smem_u32(smem_raw);
  const int tid = __shfl_sync(0xffffffffu, (int)threadIdx.x, threadIdx.x & 31);
  const int warp = __shfl_sync(0xffffffffu, tid >> 5, 0), lane = tid & 31;
  const int rank = blockIdx.x & 15;
  const int cl = blockIdx.x >> 4;
  const int bid = cl * 16 + rank;
  const int gi = rank >> 1, a = rank & 1, head = cl * 8 + gi;
  const uint32_t t0 = clk32();
  const uint32_t bar = sb + SM_BAR;
  const uint32_t sl = sb + lane * 16;
  TR_T(trs);
  auto krow = [&](int sp) { const int idx = sp >> 1; const int p = idx < 8 ? ((gi + idx) & 7) : 8; return 288 * a + 32 * p + 16 * (sp & 1); };
  if (tid == 32) atomicAdd(&g_resident, 1u);
  const int ln_r8 = ((bid & 3) * 4 + warp / 3) + (bid >> 2) * 16, ln_w = warp % 3;
  uint4 lnv[6];
  {
    const uint4* src = reinterpret_cast<const uint4*>(x_in + (size_t)(ln_r8 * 8 + (lane >> 2)) * DM) + ln_w * 24 + (lane & 3);
#pragma unroll
    for (int t = 0; t < 6; t++) lnv[t] = __ldg(src + t * 4);
  }
  if (tid >= 96) {
    const int i = tid - 96, idx = i >> 5, t = lane >> 2, j = lane & 3;
    const int p = idx < 8 ? ((gi + idx) & 7) : 8;
    const uint32_t* src = reinterpret_cast<const uint32_t*>(mem0 + t * DM + 288 * a + 32 * p + 2 * j);
    sts128(sb + SM_MEM + i * 16, src[0], src[4], src[8], src[12]);
    if (i < 216) sts128(sb + SM_MB + i * 16, 0, 0, 0, 0);
  }
  PROF0(39);
  if (tid >= 64 && tid < 68) asm volatile("prefetch.tensormap [%0];" :: "l"(&maps.q + (tid - 64)) : "memory");
  if (warp == 0) {
    if (lane == 0) {
      mbar_init(bar + B_AG, 2); mbar_init(bar + B_AG + 8, 1); mbar_init(bar + B_AG + 16, 1); mbar_init(bar + B_AG + 24, 1); mbar_init(bar + B_AG + 32, 2);
      mbar_init(bar + B_XQK, 1); mbar_init(bar + B_XV, 9); mbar_init(bar + B_RS, 2); mbar_init(bar + B_KV, 1); mbar_init(bar + B_L, 1);
      for (int i = 0; i < 5; i++) mbar_init(bar + B_W + i * 8, 1);
      asm volatile("fence.mbarrier_init.release.cluster;" ::: "memory");
      mbar_expect(bar + B_W, 20 * SLOT); mbar_expect(bar + B_W + 8, 16 * SLOT); mbar_expect(bar + B_W + 16, 9 * SLOT);
      mbar_expect(bar + B_W + 24, 5 * 16384); mbar_expect(bar + B_W + 32, 9 * SLOT);
    }
    __syncwarp();
  }
  {
    const int g = lane >> 2, j = lane & 3;
    const uint32_t red = sb + SM_S + (warp / 3) * 256;
    float f[48];
#pragma unroll
    for (int t = 0; t < 6; t++) {
      f[t * 8 + 0] = bflo(lnv[t].x); f[t * 8 + 1] = bfhi(lnv[t].x); f[t * 8 + 2] = bflo(lnv[t].y); f[t * 8 + 3] = bfhi(lnv[t].y);
      f[t * 8 + 4] = bflo(lnv[t].z); f[t * 8 + 5] = bfhi(lnv[t].z); f[t * 8 + 6] = bflo(lnv[t].w); f[t * 8 + 7] = bfhi(lnv[t].w);
    }
    float sum = 0.f;
#pragma unroll
    for (int i = 0; i < 48; i++) sum += f[i];
    sum += __shfl_xor_sync(~0u, sum, 1); sum += __shfl_xor_sync(~0u, sum, 2);
    if (j == 0) sts32(red + g * 16 + ln_w * 4, __float_as_uint(sum));
    PROF0(40);
    __syncthreads();
    uint4 r = lds128(red + g * 16);
    const float mean = (__uint_as_float(r.x) + __uint_as_float(r.y) + __uint_as_float(r.z)) * (1.f / DM);
    float q = 0.f;
#pragma unroll
    for (int i = 0; i < 48; i++) { f[i] -= mean; q = fmaf(f[i], f[i], q); }
    q += __shfl_xor_sync(~0u, q, 1); q += __shfl_xor_sync(~0u, q, 2);
    if (j == 0) sts32(red + 128 + g * 16 + ln_w * 4, __float_as_uint(q));
    __syncthreads();
    r = lds128(red + 128 + g * 16);
    const float rs = rsqrtf((__uint_as_float(r.x) + __uint_as_float(r.y) + __uint_as_float(r.z)) * (1.f / DM) + 1e-5f);
    uint4* dst = g_xnT + ((size_t)(ln_r8 >> 4) * 9 + ln_w * 3) * 1024 + (ln_r8 & 15) * 64 + j * 8 + g;
#pragma unroll
    for (int t = 0; t < 6; t++)
      stg128(dst + (t >> 1) * 1024 + (t & 1) * 32, pack2(f[t * 8] * rs, f[t * 8 + 1] * rs), pack2(f[t * 8 + 2] * rs, f[t * 8 + 3] * rs),
             pack2(f[t * 8 + 4] * rs, f[t * 8 + 5] * rs), pack2(f[t * 8 + 6] * rs, f[t * 8 + 7] * rs));
  }
  PROF0(41);
  __syncthreads();
  if (tid == 352) {
    asm volatile("red.release.gpu.global.add.u32 [%0], 1;" :: "l"(&g_cntX[bid < 4 ? 0 : 32]) : "memory");
  }
  __syncwarp();
  __syncwarp();
  PROF0(42);
  cluster_sync();
  PROF0(43);
  if (warp < 3) {
    if (lane == 0) {
      if (warp != 1) {
        const int m = warp >> 1;
        const CUtensorMap* mp = m ? &maps.q : &maps.k;
        for (int u = 0; u < 10; u++) tma3d(sb + SM_WO + (2 * u + 1 - m) * SLOT, mp, krow(NX + u), head * 2, bar + B_W);
        for (int u = 0; u < 8; u++) tma3d(sb + SM_X + (2 * u + 1 - m) * SLOT, mp, krow(u), head * 2, bar + B_W + 8);
      } else {
        for (int u = 0; u < 9; u++) tma3d(sb + SM_V2 + (4 + u) * SLOT, &maps.v, krow(NV2 + u), head * 2, bar + B_W + 16);
        for (int u = 0; u < 4; u++) tma3d(sb + SM_V2 + u * SLOT, &maps.v, krow(u), head * 2, bar + B_W + 32);
      }
    }
    __syncwarp();
  }
  if (tid >= 96 && tid < 352 + 32) {
    const int i = tid - 96;
#pragma unroll
    for (int m = 0; m < 4; m++) {
      const char* p = (const char*)(m == 0 ? Wk : m == 1 ? Wv : m == 2 ? Wq : Wo) + ((size_t)bid * 576 + i) * 128;
      asm volatile("prefetch.global.L2 [%0];" :: "l"(p));
      asm volatile("prefetch.global.L2 [%0];" :: "l"(p + 288 * 128));
    }
  }

  if (warp < 8) {
    asm volatile("setmaxnreg.inc.sync.aligned.u32 %0;" :: "n"(REG_C));
    const int w = warp;
    const uint32_t wl = sb + (w >> 2) * 2048 + frag_off(lane, w & 3);
    const uint32_t wo = sb + SM_WO + (w >> 1) * 16384 + frag_off(lane, (w & 1) * 2);
    uint32_t Pqk[18 - NX][2][4], Pv[NPV][4];
    uint32_t Xqk[NX][2][4];
#pragma unroll
    for (int u = 0; u < 20; u++) for (int q = 0; q < 4; q++) Pqk[u >> 1][u & 1][q] = 0;
#pragma unroll
    for (int u = 0; u < NPV; u++) for (int q = 0; q < 4; q++) Pv[u][q] = 0;
#pragma unroll
    for (int u = 0; u < 2 * NX; u++) for (int q = 0; q < 4; q++) Xqk[u >> 1][u & 1][q] = 0;
    const uint32_t partner = rank ^ 1;
    const uint32_t pd = __shfl_sync(~0u, mapa(sb, partner) - sb, 0), od = __shfl_sync(~0u, mapa(sb, 2 * w + a) - sb, 0);
    const bool late = STAGGER && w >= 4;
    const uint32_t ag = bar + B_AG + (late ? 8 : 0);

    for (int s = -1; s < NSEG; s++) {
      const uint32_t par = s & 1;
      float q0[4] = {0.f, 0.f, 0.f, 0.f}, k0[4] = {0.f, 0.f, 0.f, 0.f}, q1[4] = {0.f, 0.f, 0.f, 0.f}, k1[4] = {0.f, 0.f, 0.f, 0.f};
      uint4 B[9] = {};
      uint32_t V2[NV2][4];
      auto qk = [&](int idx) {
        const int s0 = 2 * idx, s1 = 2 * idx + 1;
        if (s0 < NX) { mma16816(q0, Xqk[s0][0], B[idx].x, B[idx].y); mma16816(k0, Xqk[s0][1], B[idx].x, B[idx].y); }
        else { mma16816(q0, Pqk[s0 - NX][0], B[idx].x, B[idx].y); mma16816(k0, Pqk[s0 - NX][1], B[idx].x, B[idx].y); }
        if (s1 < NX) { mma16816(q1, Xqk[s1][0], B[idx].z, B[idx].w); mma16816(k1, Xqk[s1][1], B[idx].z, B[idx].w); }
        else { mma16816(q1, Pqk[s1 - NX][0], B[idx].z, B[idx].w); mma16816(k1, Pqk[s1 - NX][1], B[idx].z, B[idx].w); }
      };
      mbar_wait(bar + B_AG, par, t0);
      if (w == 0) { PROF(0); PROFN(24); PROFS(); }
      B[0] = lds128(sl + SM_MEM);
      qk(0);
      ldsm4t(V2[0], wl + SM_V2); ldsm4t(V2[1], wl + SM_V2 + SLOT);
      if (late) mbar_wait(bar + B_AG + 8, par, t0);
      mbar_wait(ag + 8, par, t0);
      if (w == 0) PROF(1);
      B[1] = lds128(sl + SM_MEM + 512); B[2] = lds128(sl + SM_MEM + 1024);
      bool ok = mbar_try(ag + 16, par);
      qk(1);
      if (!ok) mbar_wait(ag + 16, par, t0);
      B[3] = lds128(sl + SM_MEM + 1536); B[4] = lds128(sl + SM_MEM + 2048);
      ok = mbar_try(ag + 24, par);
      qk(2);
      ldsm4t(V2[2], wl + SM_V2 + 2 * SLOT); ldsm4t(V2[3], wl + SM_V2 + 3 * SLOT);
      qk(3);
      if (!ok) mbar_wait(ag + 24, par, t0);
      if (w == 0) PROF(2);
      B[5] = lds128(sl + SM_MEM + 2560); B[6] = lds128(sl + SM_MEM + 3072);
      ok = mbar_try(bar + B_AG + 32, par);
      qk(4);
      ldsm4t(V2[4], wl + SM_V2 + 4 * SLOT); ldsm4t(V2[5], wl + SM_V2 + 5 * SLOT);
      qk(5);
      if (!ok) mbar_wait(bar + B_AG + 32, par, t0);
      if (w == 0) PROF(3);
      B[7] = lds128(sl + SM_MEM + 3584); B[8] = lds128(sl + SM_MEM + 4096);
      qk(6);
      ldsm4t(V2[6], wl + SM_V2 + 6 * SLOT); ldsm4t(V2[7], wl + SM_V2 + 7 * SLOT);
      qk(7);
      if (late) bar_arrive(BAR_AB, 256);
      qk(8);
      const uint32_t pq0 = pack2(q0[0] + q1[0], q0[1] + q1[1]);
      {
        const uint32_t c0 = movmat(pq0), c1 = movmat(pack2(q0[2] + q1[2], q0[3] + q1[3]));
        const uint32_t c2 = movmat(pack2(k0[0] + k1[0], k0[1] + k1[1])), c3 = movmat(pack2(k0[2] + k1[2], k0[3] + k1[3]));
        const bool swp = sl & 128;
        const uint32_t y0 = swp ? c2 : c0, y1 = swp ? c3 : c1, y2 = swp ? c0 : c2, y3 = swp ? c1 : c3;
        if (s >= 0) st_async16(sl + (pd + w * 512 + SM_XQK), y0, y1, y2, y3, bar + pd + B_XQK);
        sts128(sl + (w * 512 + SM_OQK), y0, y1, y2, y3);
        bar_arrive(BAR_OQK, NTHREADS);
      }
      if (w == 0) PROF(4);
      if (w == 4) PROF(14);
      ldsm4t(V2[8], wl + SM_V2 + 8 * SLOT);
      if (STAGGER && !late) bar_sync(BAR_AB, 256);
      const float vz = __uint_as_float(pq0 & zero);
      float v[4][4] = {{vz, 0.f, 0.f, 0.f}, {vz, 0.f, 0.f, 0.f}, {vz, 0.f, 0.f, 0.f}, {vz, 0.f, 0.f, 0.f}};
      uint32_t WO[16][4];
      if (s == 0) mbar_wait(bar + B_W + 24, 0, t0);
#pragma unroll
      for (int idx = 0; idx < 9; idx++) {
        const int s0 = 2 * idx, s1 = 2 * idx + 1;
        if (s0 < NV2) mma16816(v[s0 & 3], V2[s0], B[idx].x, B[idx].y); else mma16816(v[s0 & 3], Pv[s0 - NV2], B[idx].x, B[idx].y);
        if (s1 < NV2) mma16816(v[s1 & 3], V2[s1], B[idx].z, B[idx].w); else mma16816(v[s1 & 3], Pv[s1 - NV2], B[idx].z, B[idx].w);
        if (idx >= 9 - WEARLY) ldsm4t(WO[idx - (9 - WEARLY)], wo + (idx - (9 - WEARLY)) * 2048);
      }
      {
        const uint32_t vo0 = pack2((v[0][0] + v[1][0]) + (v[2][0] + v[3][0]), (v[0][1] + v[1][1]) + (v[2][1] + v[3][1]));
        const uint32_t vo1 = pack2((v[0][2] + v[1][2]) + (v[2][2] + v[3][2]), (v[0][3] + v[1][3]) + (v[2][3] + v[3][3]));
        const uint32_t l8 = (sl - sb) >> 1;
        if (s >= 0) st_async8(l8 + (sb + pd + w * 256 + SM_XV), vo0, vo1, bar + pd + B_XV);
        sts64(l8 + (sb + w * 256 + SM_OV), vo0, vo1);
        __syncwarp();
        mbar_arrive_if(bar + B_XV, sl == sb && s >= 0);
      }
      if (w == 0) PROF(5);
      if (s == NSEG - 1) break;
#pragma unroll
      for (int u = WEARLY; u < 16; u++) ldsm4t(WO[u], dep(u >= 8 ? wo ^ 32 : wo, WO[(u < 16 - WLATE ? u : 16 - WLATE) - 1][0], zero) + (u & 7) * 2048);
      if (w == 0) PROF(6);
      bar_sync(BAR_O, NTHREADS);
      {
        float m0[4] = {0.f, 0.f, 0.f, 0.f}, m1[4] = {0.f, 0.f, 0.f, 0.f}, m2[4] = {0.f, 0.f, 0.f, 0.f}, m3[4] = {0.f, 0.f, 0.f, 0.f};
        uint32_t ob[4][4];
        bool okl = false;
#pragma unroll
        for (int u = 0; u < 4; u++) ldsm4t(ob[u], sl + SM_O + u * 512);
#pragma unroll
        for (int u = 0; u < 3; u++) {
          mma16816(m0, WO[2 * u], ob[u][0], ob[u][1]);     mma16816(m1, WO[8 + 2 * u], ob[u][0], ob[u][1]);
          mma16816(m2, WO[2 * u + 1], ob[u][2], ob[u][3]); mma16816(m3, WO[8 + 2 * u + 1], ob[u][2], ob[u][3]);
          if (u == 0) okl = mbar_try(bar + B_L, par);
        }
        if (!okl) mbar_wait(bar + B_L, par, t0);
        const uint2 iv = lds64(sb + SM_INV + ((sl >> 1) & 24));
        mma16816(m0, WO[6], ob[3][0], ob[3][1]); mma16816(m1, WO[14], ob[3][0], ob[3][1]);
        mma16816(m2, WO[7], ob[3][2], ob[3][3]); mma16816(m3, WO[15], ob[3][2], ob[3][3]);
        const float i0 = __uint_as_float(iv.x), i1 = __uint_as_float(iv.y);
        const uint32_t c0 = movmat(pack2((m0[0] + m2[0]) * i0, (m0[1] + m2[1]) * i1)), c1 = movmat(pack2((m0[2] + m2[2]) * i0, (m0[3] + m2[3]) * i1));
        const uint32_t c2 = movmat(pack2((m1[0] + m3[0]) * i0, (m1[1] + m3[1]) * i1)), c3 = movmat(pack2((m1[2] + m3[2]) * i0, (m1[3] + m3[3]) * i1));
        if (w == gi) {
          sts128(sl + SM_RS + gi * 576, c0, c1, c2, c3);
          __syncwarp();
          mbar_arrive_if(bar + B_RS, sl == sb && s >= 0);
        } else if (s >= 0) {
          st_async16(sl + (od + SM_RS + gi * 576), c0, c1, c2, c3, bar + od + B_RS);
        }
      }
      if (w == 0) PROF(10);
      if (w == 4) PROF(15);
      if (s < 0) {
        if (w == 3) PROF1(44);
        mbar_wait(bar + B_W, 0, t0);
#pragma unroll
        for (int u = 0; u < 20; u++) ldsm4t(Pqk[u >> 1][u & 1], wl + SM_WO + u * SLOT);
        mbar_wait(bar + B_W + 16, 0, t0);
#pragma unroll
        for (int u = 0; u < NPV; u++) ldsm4t(Pv[u], wl + SM_V2 + (4 + u) * SLOT);
        if (w == 3) PROF1(45);
        bar_sync(BAR_C, 256);
        if (w == 0) {
          if (lane < 5) tma3d(sb + SM_V2 + (4 + lane) * SLOT, &maps.v, krow(4 + lane), head * 2, bar + B_W + 32);
          else if (lane < 10) tma2d(sb + SM_WO + (lane - 5) * 16384, &maps.o, 288 * a + 64 * (lane - 5), head * DH, bar + B_W + 24);
          __syncwarp();
        }
        bar_arrive(BAR_ALL, NTHREADS);
        mbar_wait(bar + B_W + 8, 0, t0);
        mbar_wait(bar + B_W + 32, 0, t0);
      }
      uint32_t keep = 0;
#pragma unroll
      for (int u = 0; u < 2 * NX; u++) {
        if (u == 6) mbar_wait(bar + B_RS, par, t0);
        if (u == 7 || u == 15) { float dz[4] = {0.f, 0.f, 0.f, 0.f}; mma16816(dz, Xqk[(u - 1) >> 1][(u - 1) & 1], zero, zero); keep = __float_as_uint(dz[0]); }
        ldsm4t(Xqk[u >> 1][u & 1], (u < 1 ? wl : dep(wl, (u == 7 || u == 15) && KEEPALIVE ? keep : Xqk[(u - 1) >> 1][(u - 1) & 1][0], zero)) + SM_X + u * SLOT);
      }
      if (w == 0) PROF(11);
    }
    __syncwarp();
    cluster_sync();
  } else {
    asm volatile("setmaxnreg.dec.sync.aligned.u32 %0;" :: "n"(REG_A));
    const int x = warp - 8;
    const int g = lane >> 2, j = lane & 3;
    const uint32_t sa = sb + SM_S + x * 512 + (32 * j + 4 * (g >> 1) + (g & 1)) * 4;
    const uint32_t sq = sl + (lane & 8);
    if (x < 2) {
      bar_arrive(BAR_ALL, NTHREADS);
      for (int s = -1; s < NSEG - 1; s++) {
        const uint32_t par = s & 1;
        uint4 R[8];
        if (s == 0) mbar_wait(bar + B_W + 24, 0, t0);
        mbar_wait(bar + B_KV, par, t0);
#pragma unroll
        for (int u = 0; u < 8; u++) R[u] = lds128(sl + SM_KX + x * 4096 + u * 512);
        float c0[4] = {0.f, 0.f, 0.f, 0.f}, c1[4] = {0.f, 0.f, 0.f, 0.f}, c2[4] = {0.f, 0.f, 0.f, 0.f}, c3[4] = {0.f, 0.f, 0.f, 0.f};
        bar_sync(BAR_OQK, NTHREADS);
        {
          uint2 b[8];
#pragma unroll
          for (int u = 0; u < 8; u++) b[u] = lds64(sq + SM_OQK + u * 512);
          mmaq(c0, R[0], b[0].x, b[0].y); mmaq(c1, R[1], b[1].x, b[1].y); mmaq(c2, R[2], b[2].x, b[2].y); mmaq(c3, R[3], b[3].x, b[3].y);
          mmaq(c0, R[4], b[4].x, b[4].y); mmaq(c1, R[5], b[5].x, b[5].y); mmaq(c2, R[6], b[6].x, b[6].y); mmaq(c3, R[7], b[7].x, b[7].y);
        }
        if (x == 0) PROF(16);
        mbar_wait(bar + B_XQK, par, t0);
        if (x == 0) PROF(17);
        {
          uint2 b[8];
#pragma unroll
          for (int u = 0; u < 8; u++) b[u] = lds64(sq + SM_XQK + u * 512);
          mmaq(c0, R[0], b[0].x, b[0].y); mmaq(c1, R[1], b[1].x, b[1].y); mmaq(c2, R[2], b[2].x, b[2].y); mmaq(c3, R[3], b[3].x, b[3].y);
          mmaq(c0, R[4], b[4].x, b[4].y); mmaq(c1, R[5], b[5].x, b[5].y); mmaq(c2, R[6], b[6].x, b[6].y); mmaq(c3, R[7], b[7].x, b[7].y);
        }
        sts32(sa, __float_as_uint((c0[0] + c1[0]) + (c2[0] + c3[0])));
        sts32(sa + 64, __float_as_uint((c0[1] + c1[1]) + (c2[1] + c3[1])));
        sts32(sa + 8, __float_as_uint((c0[2] + c1[2]) + (c2[2] + c3[2])));
        sts32(sa + 72, __float_as_uint((c0[3] + c1[3]) + (c2[3] + c3[3])));
        if (x == 0) PROF(18);
        uint32_t WX[8][4];
        softmax_pv<true>(s, x, sb, sl, bar, lane, a, head, t0, WX, x == 0);
        {
          float m0[4] = {0.f, 0.f, 0.f, 0.f}, m1[4] = {0.f, 0.f, 0.f, 0.f}, m2[4] = {0.f, 0.f, 0.f, 0.f}, m3[4] = {0.f, 0.f, 0.f, 0.f};
          uint32_t ob[4][4];
#pragma unroll
          for (int u = 0; u < 4; u++) ldsm4t(ob[u], sl + SM_O + u * 512);
          const int ln = opaque(lane);
          const uint32_t r_rs2 = mapa(sb + SM_RS + gi * 576 + (32 + (ln & 3)) * 16 + x * 8, 2 * (ln >> 2) + a), r_rsb2 = mapa(bar + B_RS, 2 * (ln >> 2) + a);
          mma16816(m0, WX[0], ob[0][0], ob[0][1]); mma16816(m1, WX[1], ob[0][2], ob[0][3]);
          mma16816(m2, WX[2], ob[1][0], ob[1][1]); mma16816(m3, WX[3], ob[1][2], ob[1][3]);
          mma16816(m0, WX[4], ob[2][0], ob[2][1]); mma16816(m1, WX[5], ob[2][2], ob[2][3]);
          mma16816(m2, WX[6], ob[3][0], ob[3][1]); mma16816(m3, WX[7], ob[3][2], ob[3][3]);
          mbar_wait(bar + B_L, par, t0);
          const uint2 iv = lds64(sb + SM_INV + (ln & 3) * 8);
          const float i0 = __uint_as_float(iv.x), i1 = __uint_as_float(iv.y);
          const uint32_t d0 = movmat(pack2(((m0[0] + m1[0]) + (m2[0] + m3[0])) * i0, ((m0[1] + m1[1]) + (m2[1] + m3[1])) * i1));
          const uint32_t d1 = movmat(pack2(((m0[2] + m1[2]) + (m2[2] + m3[2])) * i0, ((m0[3] + m1[3]) + (m2[3] + m3[3])) * i1));
          if (s >= 0) st_async8(r_rs2, d0, d1, r_rsb2);
        }
        if (x == 0) PROF(19);
        reduce_exchange(x, gi, a, s, sb, bar, lane, t0, x == 0, bid);
      }
      bar_sync(BAR_OQK, NTHREADS);
    } else {
      const unsigned epoch = g_epoch + 1;
      const uint4* kx_g = g_Kf + (size_t)head * 128 * 256;
      const uint4* vx_g = g_Vf + (size_t)head * NSEG * 512;
      const int hh = x - 2;
      const uint32_t sm_ = sa - hh * 512 + hh * 8;
      uint4* const km_ptr = g_Kmf + (size_t)head * NSEG * 128 + hh * 64 + lane;
      if (x == 2) bar_arrive(BAR_ALL, NTHREADS);
      for (int s = -1; s < NSEG; s++) {
        const uint32_t par = s & 1;
        uint2 Q[4], K[4], oq[4], okk[4];
        if (s < NSEG - 1) mbar_wait(bar + B_KV, par, t0);
        bar_sync(BAR_OQK, NTHREADS);
#pragma unroll
        for (int u = 0; u < 4; u++) { Q[u] = lds64(sq + SM_OQK + (hh * 4 + u) * 512); K[u] = lds64((sq ^ 8) + SM_OQK + (hh * 4 + u) * 512); }
        mbar_wait(bar + B_XQK, par, t0);
        float c0[4] = {0.f, 0.f, 0.f, 0.f}, c1[4] = {0.f, 0.f, 0.f, 0.f}, c2[4] = {0.f, 0.f, 0.f, 0.f}, c3[4] = {0.f, 0.f, 0.f, 0.f};
#pragma unroll
        for (int u = 0; u < 4; u++) { oq[u] = lds64(sq + SM_XQK + (hh * 4 + u) * 512); okk[u] = lds64((sq ^ 8) + SM_XQK + (hh * 4 + u) * 512); }
#pragma unroll
        for (int u = 0; u < 4; u++) {
          Q[u].x = hadd2bf(Q[u].x, oq[u].x); Q[u].y = hadd2bf(Q[u].y, oq[u].y); K[u].x = hadd2bf(K[u].x, okk[u].x); K[u].y = hadd2bf(K[u].y, okk[u].y);
        }
#pragma unroll
        for (int u = 0; u < 4; u += 2) {
          mma1688(c0, K[u].x, K[u].y, Q[u].x);
          mma1688(c1, K[u].x, K[u].y, Q[u].y);
          mma1688(c2, K[u + 1].x, K[u + 1].y, Q[u + 1].x);
          mma1688(c3, K[u + 1].x, K[u + 1].y, Q[u + 1].y);
        }
        sts32(sm_, __float_as_uint((c0[0] + c1[2]) + (c2[0] + c3[2])));
        sts32(sm_ + 64, __float_as_uint((c0[1] + c1[3]) + (c2[1] + c3[3])));
        uint32_t dummy[8][4];
        if (s < NSEG - 1) softmax_pv<false>(s, x, sb, sl, bar, lane, a, head, t0, dummy, 0);
        if (a == 0 && s >= 0) {
          km_ptr[(size_t)s * 128] = make_uint4(K[0].x, K[0].y, K[1].x, K[1].y);
          km_ptr[(size_t)s * 128 + 32] = make_uint4(K[2].x, K[2].y, K[3].x, K[3].y);
        }
        if (s == NSEG - 1) break;
        if (x == 2) {
          reduce_exchange(x, gi, a, s, sb, bar, lane, t0, 0, bid);
          if (lane == 0) mbar_expect(bar + B_RS, RS_BYTES);
        } else {
          if (lane == 0 && s >= 0 && s + 1 < NSEG - 1) {
            mbar_expect(bar + B_KV, 16384);
            bulk_g2s(sb + SM_KX, kx_g + (size_t)(s + 1) * 512, 8192, bar + B_KV);
            bulk_g2s(sb + SM_VX, vx_g + (size_t)(s + 1) * 512, 8192, bar + B_KV);
          }
          __syncwarp();
          mbar_wait(bar + B_RS, par, t0);
          if (lane == 0) {
            const int nb = s < 0 ? 0 : 1024;
            mbar_expect(bar + B_AG + 8, nb); mbar_expect(bar + B_AG + 16, nb); mbar_expect(bar + B_AG + 24, nb); mbar_expect(bar + B_AG + 32, s < 0 ? 0 : 960);
            mbar_expect(bar + B_XQK, 4096); mbar_expect(bar + B_XV, 2048);
            if (a == 0 && (s & 3) == 0 && s > 0) { st_release(&g_memflag[head * 8], epoch * 64 + s); if (bid == 0) TR_LOG(9 | (((s - 1) >> 2) << 24), trs, trs); }
            if ((s & 3) == 2 && s + 2 < NSEG) {
              while (ld_acquire(&g_kvflag[((s + 2) >> 2) * 64 + head]) != epoch) { if (timed_out(t0)) break; }
              while (ld_acquire(&g_kvflag[((s + 2) >> 2) * 64 + 32 + head]) != epoch) { if (timed_out(t0)) break; }
              asm volatile("fence.proxy.async.global;" ::: "memory");
              asm volatile("cp.async.bulk.prefetch.L2.global [%0], 32768;" :: "l"(kx_g + (size_t)(s + 2) * 512) : "memory");
              asm volatile("cp.async.bulk.prefetch.L2.global [%0], 32768;" :: "l"(vx_g + (size_t)(s + 2) * 512) : "memory");
            }
          }
          __syncwarp();
          if (s >= 0) {
            float dz[4] = {0.f, 0.f, 0.f, 0.f};
            while (true) {
              mma16816(dz, zero, zero, zero, zero, zero, zero);
              if (__all_sync(~0u, mbar_test(bar + B_AG + __float_as_uint(dz[0]), par ^ 1) || timed_out(t0))) break;
              __nanosleep(KEEPALIVE);
            }
          }
          if (s < 0) {
            __syncwarp();
            bar_sync(BAR_ALL, NTHREADS);
            if (lane == 0) {
              while (ld_acquire(&g_kvflag[head]) != epoch) { if (timed_out(t0)) break; __nanosleep(100); }
              while (ld_acquire(&g_kvflag[32 + head]) != epoch) { if (timed_out(t0)) break; __nanosleep(100); }
              asm volatile("fence.proxy.async.global;" ::: "memory");
              mbar_expect(bar + B_KV, 16384);
              bulk_g2s(sb + SM_KX, kx_g, 8192, bar + B_KV);
              bulk_g2s(sb + SM_VX, vx_g, 8192, bar + B_KV);
            }
          }
        }
        __syncwarp();
      }
    }
    {
      mbar_wait(bar + B_XV, (NSEG - 1) & 1, t0);
      const uint32_t lv = sb + x * 512 + lane * 8;
      const uint2 ov0 = lds64(lv + SM_OV), xv0 = lds64(lv + SM_XV), ov1 = lds64(lv + SM_OV + 256), xv1 = lds64(lv + SM_XV + 256);
      if (a == 0) g_Vmf[((size_t)head * NSEG + NSEG - 1) * 128 + x * 32 + lane] = make_uint4(hadd2bf(ov0.x, xv0.x), hadd2bf(ov0.y, xv0.y), hadd2bf(ov1.x, xv1.x), hadd2bf(ov1.y, xv1.y));
      bar_sync(BAR_S, 128);
      if (x == 3 && a == 0 && lane == 0) { st_release(&g_memflag[head * 8], (g_epoch + 1) * 64 + 64); if (bid == 0) TR_LOG(9 | (15 << 24), trs, trs); }
    }
    __syncwarp();
    cluster_sync();
  }
}
}
__device__ __align__(1024) uint4 g_hnT[NRB * 9 * 1024];
__device__ __align__(1024) uint4 g_oT[NRB * 64 * 1024];
__device__ __align__(1024) uint4 g_gT[NRB * 72 * 1024];
constexpr int MAXSPLIT = 8;
__device__ __align__(1024) uint4 g_p1[MAXSPLIT * 256 * 18 * 32];
__device__ __align__(1024) uint4 g_p2[MAXSPLIT * 256 * 18 * 32];
__device__ __align__(1024) uint4 g_hT[256 * 18 * 32];

__global__ void gate_kernel() {
  const uint32_t t0 = clk32();
  const unsigned need = (g_epoch + 1) * 64u;
  while ((int)(ld_acquire(&g_resident) - need) < 0) { if (timed_out(t0)) break; }
}
namespace mega {
constexpr int NS = 5;
constexpr int SM_B = 0, SM_A = 9 * 16384, SM_BAR = SM_A + NS * 16384;
constexpr int B_FA = 0, B_EA = NS * 8, B_FB = 2 * NS * 8, B_EB = B_FB + 96, B_D = B_EB + 24, B_TK = B_D + 32, B_QF = B_TK + 32, B_QE = B_QF + 16,
              B_PD = B_QE + 16, B_PE = B_PD + 16;
constexpr int SM_DESC = SM_BAR + 512;
constexpr int SM_TQ = SM_DESC + 64;
constexpr int SM_TK = SM_TQ + 32;
constexpr int SM_PUB = SM_TK + 16;
constexpr int SM_RED = SM_PUB + 16;
constexpr int SM_TOTAL = SM_RED + 256;
enum { T_K = 0, T_V = 1, T_QA = 2, T_OP = 3, T_F1 = 4, T_F2 = 5, T_END = 6 };
constexpr int NORDER = 474;
__constant__ unsigned short c_order[NORDER] = {
  386,1410,2434,3458,4482,5506,6530,7554,8578,9602,10626,11650,12674,13698,14722,15746,387,1411,2435,3459,
  4483,5507,6531,7555,8579,9603,10627,11651,12675,13699,14723,15747,16771,17795,410,1434,2458,3482,4506,5530,
  6554,7578,8602,9626,10650,11674,12698,13722,14746,15770,388,1412,2436,3460,4484,5508,6532,7556,8580,9604,
  10628,11652,12676,13700,14724,15748,16772,17796,411,1435,2459,3483,4507,5531,6555,7579,8603,9627,10651,11675,
  12699,13723,14747,15771,16795,17819,389,1413,2437,3461,4485,5509,6533,7557,8581,9605,10629,11653,12677,13701,
  14725,15749,16773,17797,434,1458,2482,3506,4530,5554,6578,7602,8626,9650,10674,11698,12722,13746,14770,15794,
  412,1436,2460,3484,4508,5532,6556,7580,8604,9628,10652,11676,12700,13724,14748,15772,16796,17820,435,1459,
  2483,3507,4531,5555,6579,7603,8627,9651,10675,11699,12723,13747,14771,15795,16819,17843,413,1437,2461,3485,
  4509,5533,6557,7581,8605,9629,10653,11677,12701,13725,14749,15773,16797,17821,458,1482,2506,3530,4554,5578,
  6602,7626,8650,9674,10698,11722,12746,13770,14794,15818,436,1460,2484,3508,4532,5556,6580,7604,8628,9652,
  10676,11700,12724,13748,14772,15796,16820,17844,459,1483,2507,3531,4555,5579,6603,7627,8651,9675,10699,11723,
  12747,13771,14795,15819,16843,17867,437,1461,2485,3509,4533,5557,6581,7605,8629,9653,10677,11701,12725,13749,
  14773,15797,16821,17845,354,1378,2402,3426,4450,5474,6498,7522,8546,9570,10594,11618,12642,13666,14690,15714,
  460,1484,2508,3532,4556,5580,6604,7628,8652,9676,10700,11724,12748,13772,14796,15820,16844,17868,370,1394,
  2418,3442,4466,5490,6514,7538,8562,9586,10610,11634,12658,13682,14706,15730,355,1379,2403,3427,4451,5475,
  6499,7523,8547,9571,10595,11619,12643,13667,14691,15715,16739,17763,243,1267,2291,3315,4339,5363,6387,7411,
  8435,9459,10483,11507,12531,13555,14579,15603,16627,17651,251,1275,2299,3323,4347,5371,6395,7419,8443,9467,
  10491,11515,12539,13563,14587,15611,16635,17659,461,1485,2509,3533,4557,5581,6605,7629,8653,9677,10701,11725,
  12749,13773,14797,15821,16845,17869,356,1380,2404,3428,4452,5476,6500,7524,8548,9572,10596,11620,12644,13668,
  14692,15716,16740,17764,244,1268,2292,3316,4340,5364,6388,7412,8436,9460,10484,11508,12532,13556,14580,15604,
  16628,17652,252,1276,2300,3324,4348,5372,6396,7420,8444,9468,10492,11516,12540,13564,14588,15612,16636,17660,
  357,1381,2405,3429,4453,5477,6501,7525,8549,9573,10597,11621,12645,13669,14693,15717,16741,17765,245,1269,
  2293,3317,4341,5365,6389,7413,8437,9461,10485,11509,12533,13557,14581,15605,16629,17653,253,1277,2301,3325,
  4349,5373,6397,7421,8445,9469,10493,11517,12541,13565,14589,15613,16637,17661,
};
constexpr int NTASK = 32 + NORDER;
constexpr int NWTASK = 2048;
constexpr int SPL = 6;
#define PRE 6
#define PFA 0
#define PFB 0
constexpr int REG_C = 192, REG_P = 120;
static_assert(2 * REG_C + REG_P <= 504, "register pool");

__device__ unsigned g_ticket, g_wticket;
constexpr int PAD = 32;
__device__ unsigned g_cntO[NRB * 8 * PAD], g_cntP1[NRB * PAD], g_cntH[NRB * PAD], g_cntG[NRB * 8 * PAD], g_cntP2[NRB * PAD], g_done;

template <int B> struct IntC { static constexpr int value = B; };
__device__ __forceinline__ void red_release(unsigned* p) { asm volatile("red.release.gpu.global.add.u32 [%0], 1;" :: "l"(p) : "memory"); }
__device__ __forceinline__ void wait_cnt(const unsigned* p, unsigned need, int far, uint32_t t0) {
  while (true) {
    const int d = (int)(ld_relaxed(p) - need);
    if (d >= 0) break;
    if (timed_out(t0)) break;
    __nanosleep(d <= -far ? 1000 : 40);
  }
  (void)ld_acquire(p);
}
__device__ __forceinline__ float gelu_tanh(float z) {
  const float u = z * fmaf(z * z, 0.044715f * 0.7978845608028654f, 0.7978845608028654f);
  float t; asm("tanh.approx.f32 %0, %1;" : "=f"(t) : "f"(u));
  const float hz = 0.5f * z;
  return fmaf(hz, t, hz);
}
__device__ __forceinline__ void acc8(float (&f)[8], const uint4& v) {
  f[0] += bflo(v.x); f[1] += bfhi(v.x); f[2] += bflo(v.y); f[3] += bfhi(v.y);
  f[4] += bflo(v.z); f[5] += bfhi(v.z); f[6] += bflo(v.w); f[7] += bfhi(v.w);
}

__device__ __forceinline__ void arrive2_if(uint32_t local, uint32_t pd, int p, int cnt) {
  asm volatile("{ .reg .pred q; setp.ne.b32 q, %2, 0; @q mbarrier.arrive.shared::cta.b64 _, [%0], %3; @q mbarrier.arrive.shared::cluster.b64 _, [%1], %3; }"
    :: "r"(local), "r"(local + pd), "r"(p), "r"(cnt) : "memory");
}
__device__ __forceinline__ void bulk_mc(uint32_t dst, const void* src, uint32_t bytes, uint32_t bar) {
  asm volatile("cp.async.bulk.shared::cluster.global.mbarrier::complete_tx::bytes.multicast::cluster [%0], [%1], %2, [%3], %4;"
    :: "r"(dst), "l"(src), "r"(bytes), "r"(bar), "h"((uint16_t)3) : "memory");
}
__device__ __forceinline__ int op_kb0(int kc) { return kc < 2 ? 12 * kc : 4 + 10 * kc; }
__device__ __forceinline__ int task_nkb(int type, int kc) { return type == T_OP ? (kc < 2 ? 12 : 10) : type == T_F2 ? 12 : 9; }

__device__ __forceinline__ void finish(unsigned epoch) {
  if (atomicAdd(&g_done, 1u) == epoch * 3 * gridDim.x - 1) { g_ticket = 0; g_wticket = 0; g_epoch = epoch; }
}
struct Maps { CUtensorMap m[6]; CUtensorMap pf[4]; };

__global__ void __launch_bounds__(384, 1)
mega_kernel(const __grid_constant__ Maps maps, const bf16* __restrict__ x, const bf16* __restrict__ b1, const bf16* __restrict__ b2,
            bf16* __restrict__ out) {
  extern __shared__ __align__(1024) unsigned char smem_raw[];
  const uint32_t sb = smem_u32(smem_raw);
  const int tid = threadIdx.x, wg = __shfl_sync(~0u, tid >> 7, 0), lane = tid & 31, w = __shfl_sync(~0u, (tid >> 5) & 3, 0);
  const uint32_t bar = sb + SM_BAR;
  const uint32_t t0 = clk32();
  if (tid == 0) {
    for (int i = 0; i < NS; i++) { mbar_init(bar + B_FA + i * 8, 1); mbar_init(bar + B_EA + i * 8, 8); }
    for (int i = 0; i < 12; i++) mbar_init(bar + B_FB + i * 8, 1);
    for (int i = 0; i < 3; i++) mbar_init(bar + B_EB + i * 8, 4);
    for (int i = 0; i < 4; i++) mbar_init(bar + B_D + i * 8, 1);
    for (int i = 0; i < 4; i++) mbar_init(bar + B_TK + i * 8, 1);
    for (int i = 0; i < 2; i++) { mbar_init(bar + B_QF + i * 8, 1); mbar_init(bar + B_QE + i * 8, 1); mbar_init(bar + B_PD + i * 8, 4); mbar_init(bar + B_PE + i * 8, 1); }
    asm volatile("fence.mbarrier_init.release.cluster;" ::: "memory");
  }
  const int rank = blockIdx.x & 1;
  const uint32_t pd = __shfl_sync(~0u, mapa(sb, rank ^ 1) - sb, 0);
  const unsigned ep0 = *(volatile unsigned*)&g_epoch;
  const unsigned epoch = ep0 + 1;
  __syncthreads();
  asm volatile("barrier.cluster.arrive.relaxed.aligned; barrier.cluster.wait.aligned;" ::: "memory");
  if (wg == 2) {
    asm volatile("setmaxnreg.dec.sync.aligned.u32 %0;" :: "n"(REG_P));
    if (w == 0) {
      if (lane == 0) {
        int st = 0, ph = 1, seq = 0, qi = 0;
        auto pop = [&]() {
          mbar_wait(bar + B_QF + (qi & 1) * 8, (qi >> 1) & 1, t0);
          const uint4 e = lds128(sb + SM_TQ + (qi & 1) * 16);
          mbar_arrive(bar + B_QE + (qi & 1) * 8);
          qi++;
          return e;
        };
        while (true) {
          const uint4 e = pop();
          const int type = e.x & 255;
          if (type == T_END) break;
          const int sl = (e.x >> 8) & 255, kc = (e.x >> 16) & 255, rb = e.x >> 24;
          sts128(sb + SM_DESC + (seq & 3) * 16, e.x, e.y | st | (ph << 8), e.z, 0);
          mbar_arrive(bar + B_D + (seq & 3) * 8);
          seq++;
          const int nkb = task_nkb(type, kc), kb0 = type == T_OP ? op_kb0(kc) : kc * 12;
          const uint4* A = type <= T_QA ? g_xnT : type == T_OP ? g_oT : type == T_F1 ? g_hnT : g_gT;
          const int ktot = type == T_OP ? 64 : type == T_F2 ? 72 : 9;
          const uint4* src = A + ((size_t)rb * ktot + kb0) * 1024 + rank * 512;
          for (int kb = 0; kb < nkb; kb++) {
            mbar_wait(bar + B_EA + st * 8, ph, t0);
            mbar_expect(bar + B_FA + st * 8, 16384);
            bulk_mc(sb + SM_A + st * 16384 + rank * 8192, src + kb * 1024, 8192, bar + B_FA + st * 8);
            if (++st == NS) { st = 0; ph ^= 1; }
          }
          if (type == T_QA) {
            for (int q = 0; q < 5; q++) {
              if (q == 2) pop();
              mbar_wait(bar + B_EA + st * 8, ph, t0);
              const uint32_t fa = bar + B_FA + st * 8, dst = sb + SM_A + st * 16384;
              mbar_expect(fa, 16384);
              const size_t so = (size_t)sl * NSEG + rb * 4;
              if (q < 2) bulk_g2s(dst, g_Kf + so * 512 + q * 1024, 16384, fa);
              else if (q > 2) bulk_g2s(dst, g_Vf + so * 512 + (q - 3) * 1024, 16384, fa);
              else { bulk_g2s(dst, g_Kmf + so * 128, 8192, fa); bulk_g2s(dst + 8192, g_Vmf + so * 128, 8192, fa); }
              if (++st == NS) { st = 0; ph ^= 1; }
            }
          }
        }
        for (int i = 0; i < 2; i++) {
          sts128(sb + SM_DESC + (seq & 3) * 16, T_END, i, 0, 0);
          mbar_arrive(bar + B_D + (seq & 3) * 8);
          seq++;
        }
      }
      __syncwarp();
      asm volatile("barrier.cluster.arrive.relaxed.aligned; barrier.cluster.wait.aligned;" ::: "memory");
    } else if (w == 1) {
      if (lane == 0) {
        uint32_t fbph = 0, ebph = 1;
        int qi = 0, tk = 0, tiles = 0, pubs = 0, pub0 = 0, pub1 = 0;
        auto service = [&]() {
          bool any = false;
          if (mbar_test(bar + B_PD, pub0 & 1)) {
            const uint2 p = lds64(sb + SM_PUB);
            mbar_arrive(bar + B_PE);
            red_release(reinterpret_cast<unsigned*>(((unsigned long long)p.y << 32) | p.x));
            pub0++; pubs++; any = true;
          }
          if (mbar_test(bar + B_PD + 8, pub1 & 1)) {
            const uint2 p = lds64(sb + SM_PUB + 8);
            mbar_arrive(bar + B_PE + 8);
            red_release(reinterpret_cast<unsigned*>(((unsigned long long)p.y << 32) | p.x));
            pub1++; pubs++; any = true;
          }
          return any;
        };
        auto can_post = [&]() { return qi == 0 || mbar_test(bar + B_QE + ((qi - 1) & 1) * 8, ((qi - 1) >> 1) & 1); };
        auto post = [&](uint32_t x, uint32_t y, uint32_t z) {
          sts128(sb + SM_TQ + (qi & 1) * 16, x, y, z, 0);
          mbar_arrive(bar + B_QF + (qi & 1) * 8);
          qi++;
        };
        while (true) {
          unsigned task;
          if (rank == 0) {
            task = atomicAdd(&g_ticket, 1u);
            asm volatile("st.async.shared::cluster.mbarrier::complete_tx::bytes.b32 [%0], %1, [%2];"
              :: "r"(sb + SM_TK + (tk & 3) * 4 + pd), "r"(task), "r"(bar + B_TK + (tk & 3) * 8 + pd) : "memory");
          } else {
            mbar_expect(bar + B_TK + (tk & 3) * 8, 4);
            while (!mbar_test(bar + B_TK + (tk & 3) * 8, (tk >> 2) & 1)) { service(); if (timed_out(t0)) break; }
            asm volatile("ld.shared.b32 %0, [%1];" : "=r"(task) : "r"(sb + SM_TK + (tk & 3) * 4) : "memory");
          }
          tk++;
          if (task >= (unsigned)NTASK) break;
          int type, sl, kc = 0, rb0, n;
          if (task < 32) { type = rank; sl = task; rb0 = 0; n = NRB; }
          else {
            const int e = c_order[task - 32], r = e >> 10;
            type = e & 7; rb0 = (e >> 3) & 15; n = (e >> 7) & 7;
            if (type & 1) { kc = r / 3; sl = r % 3; } else sl = r;
            sl = 2 * sl + rank;
          }
          const bool narrow = type == T_OP || type == T_F2;
          const int nkb = task_nkb(type, kc), kb0 = type == T_OP ? op_kb0(kc) : kc * 12;
          const CUtensorMap* mp = &maps.m[type];
          auto load_third = [&](int th) {
            if (narrow) {
              for (int kb = th * 4; kb < th * 4 + 4 && kb < nkb; kb++) {
                const uint32_t fb = bar + B_FB + kb * 8, dst = sb + SM_B + kb * 12288;
                mbar_expect(fb, 12288);
                for (int p = 0; p < 3; p++) tma5d(dst + p * 4096, mp, sl * 96 + p * 32, (kb0 + kb) * 2, fb);
              }
            } else {
              for (int kb = th * 3; kb < th * 3 + 3; kb++) {
                const uint32_t fb = bar + B_FB + kb * 8, dst = sb + SM_B + kb * 16384;
                mbar_expect(fb, 16384);
                if (type <= T_QA) { tma2d(dst, mp, sl * 128, kb * 64, fb); tma2d(dst + 8192, mp, sl * 128 + 64, kb * 64, fb); }
                else { tma5d(dst, mp, sl * 128, kb * 2, fb); tma5d(dst + 8192, mp, sl * 128 + 64, kb * 2, fb); }
              }
            }
          };
          auto deps_ready = [&](int rb, bool mem) -> bool {
            if (mem) return (int)(ld_acquire(&g_memflag[sl * 8]) - (epoch * 64 + rb * 4 + 4)) >= 0;
            if (type == T_QA) return ld_acquire(&g_kvflag[rb * 64 + sl]) == epoch && ld_acquire(&g_kvflag[rb * 64 + 32 + sl]) == epoch;
            if (type == T_OP) return (int)(ld_acquire(&g_cntO[(rb * 8 + kc) * PAD]) - epoch * (nkb >> 1)) >= 0;
            if (type == T_F1) return (int)(ld_acquire(&g_cntH[rb * PAD]) - epoch * 64) >= 0;
            if (type == T_F2) return (int)(ld_acquire(&g_cntG[(rb * 8 + kc) * PAD]) - epoch * 6) >= 0;
            return rb >= 2 || (rb == 0 ? (int)(ld_acquire(&g_cntX[0]) - epoch * 4) >= 0 : (int)(ld_acquire(&g_cntX[32]) - epoch * 60) >= 0);
          };
          int th = 0, t = 0;
          bool mem = false, rdy = false;
          while (th < 3 || t < n) {
            bool prog = service();
            if (th < 3 && mbar_test(bar + B_EB + th * 8, ebph)) { load_third(th++); prog = true; }
            if (t < n) {
              const int rb = rb0 + t;
              if (!rdy && deps_ready(rb, mem)) {
                rdy = true;
                if (type > T_V || t < 2) asm volatile("fence.proxy.async.global;" ::: "memory");
              }
              if (rdy && can_post()) {
                post(type | (sl << 8) | (kc << 16) | (rb << 24), ((t == n - 1) << 16) | ((t < 2) << 17), fbph);
                rdy = false; prog = true;
                if (type == T_QA && !mem) { mem = true; tiles++; } else { if (type != T_QA) tiles++; mem = false; t++; }
              }
            }
            if (!prog) { if (timed_out(t0)) break; __nanosleep(rdy || t >= n ? 20 : 80); }
          }
          fbph ^= (1u << nkb) - 1; ebph ^= 1;
        }
        while (!can_post()) { service(); if (timed_out(t0)) break; }
        post(T_END, 0, 0);
        while (pubs < tiles) { if (!service()) { if (timed_out(t0)) break; __nanosleep(20); } }
        finish(epoch);
      }
      __syncwarp();
      asm volatile("barrier.cluster.arrive.relaxed.aligned; barrier.cluster.wait.aligned;" ::: "memory");
    } else {
      const int uq = lane >> 3, j = lane & 3;
      int id = 0;
      if (lane == 0) id = (int)atomicAdd(&g_wticket, 1u);
      id = __shfl_sync(~0u, id, 0);
      int nl = id < 128 ? (id & 1) : NRB, nf = id < 128 ? ((id & 1) ^ 1) : NRB;
      while (nl < NRB || nf < NRB) {
        int fin = 0;
        if (lane == 0) {
          while (true) {
            const int dl = nl < NRB ? (int)(ld_relaxed(&g_cntP1[nl * PAD]) - epoch * 36) : -1000;
            const int df = nf < NRB ? (int)(ld_relaxed(&g_cntP2[nf * PAD]) - epoch * 36) : -1000;
            if (dl >= -PRE) break;
            if (df >= -PRE) { fin = 1; break; }
            if (timed_out(t0)) { fin = nl >= NRB; break; }
            __nanosleep(dl <= -36 && df <= -36 ? 500 : 100);
          }
        }
        fin = __shfl_sync(~0u, fin, 0);
        const int rb = fin ? nf : nl;
        if (fin) nf += 2; else nl += 2;
        const int r2 = rb * 64 + (id >> 1), r8 = r2 >> 2;
        const int cl = (r2 & 3) * 8 + (lane & 7), g = cl >> 2;
        uint4* hp = g_hT + ((size_t)r8 * 18 + uq) * 32 + cl;
        const uint4* p = (fin ? g_p2 : g_p1) + ((size_t)r8 * 18 + uq) * (SPL * 32) + cl;
        const size_t roff = (size_t)(r8 * 8 + g) * (DM / 2) + uq * 16 + j;
        const uint32_t* e = fin ? reinterpret_cast<const uint32_t*>(b2) + uq * 16 + j : reinterpret_cast<const uint32_t*>(x) + roff;
        const bool v4 = uq < 2;
        uint4 hv[5];
#pragma unroll
        for (int t = 0; t < 5; t++) {
          hv[t] = make_uint4(0, 0, 0, 0);
          if (t < 4 || v4) hv[t] = make_uint4(ldg32(e + t * 64), ldg32(e + t * 64 + 4), ldg32(e + t * 64 + 8), ldg32(e + t * 64 + 12));
        }
        if (lane == 0) wait_cnt(fin ? &g_cntP2[rb * PAD] : &g_cntP1[rb * PAD], epoch * 36, 36, t0);
        __syncwarp();
        TR_T(tr0);
        float s = 0.f;
#pragma unroll
        for (int b = 0; b < 2; b++) {
          uint4 v[3][SPL], r[3];
#pragma unroll
          for (int t = 0; t < 3 - b; t++) {
            const int tt = b * 3 + t;
#pragma unroll
            for (int q = 0; q < SPL; q++) { v[t][q] = make_uint4(0, 0, 0, 0); if (tt < 4 || v4) v[t][q] = ldg_cg(p + (tt * 4 * SPL + q) * 32); }
          }
          if (fin) {
#pragma unroll
            for (int t = 0; t < 3 - b; t++) { const int tt = b * 3 + t; r[t] = make_uint4(0, 0, 0, 0); if (tt < 4 || v4) r[t] = ldg_cg(hp + tt * 128); }
          }
#pragma unroll
          for (int t = 0; t < 3 - b; t++) {
            const int tt = b * 3 + t;
            float f[8] = {0.f, 0.f, 0.f, 0.f, 0.f, 0.f, 0.f, 0.f};
#pragma unroll
            for (int q = 0; q < SPL; q++) acc8(f, v[t][q]);
            acc8(f, hv[tt]);
            if (fin) acc8(f, r[t]);
            const uint4 h = make_uint4(pack2(f[0], f[1]), pack2(f[2], f[3]), pack2(f[4], f[5]), pack2(f[6], f[7]));
            hv[tt] = h;
            if (tt < 4 || v4) {
              if (fin) { uint32_t* o = reinterpret_cast<uint32_t*>(out) + roff + tt * 64; o[0] = h.x; o[4] = h.y; o[8] = h.z; o[12] = h.w; }
              else stg128(hp + tt * 128, h.x, h.y, h.z, h.w);
            }
            s += ((bflo(h.x) + bfhi(h.x)) + (bflo(h.y) + bfhi(h.y))) + ((bflo(h.z) + bfhi(h.z)) + (bflo(h.w) + bfhi(h.w)));
          }
        }
        if (!fin) {
          s += __shfl_xor_sync(~0u, s, 1); s += __shfl_xor_sync(~0u, s, 2); s += __shfl_xor_sync(~0u, s, 8); s += __shfl_xor_sync(~0u, s, 16);
          const float mean = s * (1.f / DM);
          float dv[5][8];
          float q = 0.f;
#pragma unroll
          for (int t = 0; t < 5; t++) {
            dv[t][0] = bflo(hv[t].x) - mean; dv[t][1] = bfhi(hv[t].x) - mean; dv[t][2] = bflo(hv[t].y) - mean; dv[t][3] = bfhi(hv[t].y) - mean;
            dv[t][4] = bflo(hv[t].z) - mean; dv[t][5] = bfhi(hv[t].z) - mean; dv[t][6] = bflo(hv[t].w) - mean; dv[t][7] = bfhi(hv[t].w) - mean;
            float qq = 0.f;
#pragma unroll
            for (int i = 0; i < 8; i++) qq = fmaf(dv[t][i], dv[t][i], qq);
            if (t < 4 || v4) q += qq;
          }
          q += __shfl_xor_sync(~0u, q, 1); q += __shfl_xor_sync(~0u, q, 2); q += __shfl_xor_sync(~0u, q, 8); q += __shfl_xor_sync(~0u, q, 16);
          const float rs = rsqrtf(q * (1.f / DM) + 1e-5f);
          uint4* dst = g_hnT + ((size_t)rb * 9 + (uq >> 1)) * 1024 + (r8 & 15) * 64 + ((uq & 1) * 4 + j) * 8 + g;
#pragma unroll
          for (int t = 0; t < 5; t++)
            if (t < 4 || v4)
              stg128(dst + t * 2048, pack2(dv[t][0] * rs, dv[t][1] * rs), pack2(dv[t][2] * rs, dv[t][3] * rs),
                     pack2(dv[t][4] * rs, dv[t][5] * rs), pack2(dv[t][6] * rs, dv[t][7] * rs));
          __syncwarp();
          if (lane == 0) red_release(&g_cntH[rb * PAD]);
        }
        if (lane == 0 && (r2 & 3) == 0) TR_LOG((7 + fin) | ((r8 & 15) << 8) | (rb << 24), tr0, tr0);
      }
      if (lane == 0) finish(epoch);
      __syncwarp();
      asm volatile("barrier.cluster.arrive.relaxed.aligned; barrier.cluster.wait.aligned;" ::: "memory");
    }
  } else {
    asm volatile("setmaxnreg.inc.sync.aligned.u32 %0;" :: "n"(REG_C));
    const int g = lane >> 2, j = lane & 3;
    const int l0 = __shfl_sync(~0u, lane == 0, lane);
    for (int seq = wg;; seq += 2) {
      mbar_wait(bar + B_D + (seq & 3) * 8, (seq >> 2) & 1, t0);
      uint4 d = lds128(sb + SM_DESC + (seq & 3) * 16);
      d.x = __shfl_sync(~0u, d.x, 0); d.y = __shfl_sync(~0u, d.y, 0); d.z = __shfl_sync(~0u, d.z, 0);
      const int type = d.x & 255;
      const int sl = (d.x >> 8) & 255, kc = (d.x >> 16) & 255, rb = d.x >> 24;
      const int nkb = task_nkb(type, kc);
      const int last = (d.y >> 16) & 1; const bool needb = (d.y >> 17) & 1;
      int st = d.y & 255, ph = ((d.y >> 8) & 1) ^ 1, prev = 0;
      float acc[2][64];
      {
        const uint32_t* bp = reinterpret_cast<const uint32_t*>(b1 + sl * 128) + j;
#pragma unroll
        for (int i = 0; i < 16; i++) {
          uint32_t b = 0;
          if (type == T_F1) b = ldg32(bp + i * 4);
          acc[0][4 * i] = acc[0][4 * i + 2] = acc[1][4 * i] = acc[1][4 * i + 2] = bflo(b);
          acc[0][4 * i + 1] = acc[0][4 * i + 3] = acc[1][4 * i + 1] = acc[1][4 * i + 3] = bfhi(b);
        }
      }
      fence_regs(acc[0]); fence_regs(acc[1]);
      if (seq > 0) bar_sync(3 + wg, 256);
      if (type == T_END) { if (d.y == 0) bar_arrive(3 + (wg ^ 1), 256); break; }
      TR_T(tr0);
      auto mainloop = [&](auto mode) {
        constexpr int MD = decltype(mode)::value;
        constexpr int PER = MD == 2 ? 4 : 3;
        const uint64_t a_hi = make_desc(0, 128, type == T_QA ? 2048 : 1024, 0), b_hi = MD == 2 ? make_desc(0, 4096, 512, 2) : make_desc(0, 8192, 1024, 1);
        const uint32_t a_off = type == T_QA ? 64 : 512;
        bool oka = false;
        int eb = 0, ec = 0;
        for (int kb = 0; kb < nkb; kb++) {
          if (needb) mbar_wait(bar + B_FB + kb * 8, (d.z >> kb) & 1, t0);
          if (!oka) mbar_wait(bar + B_FA + st * 8, ph, t0);
          const uint64_t da = a_hi + ((((sb + SM_A) & 0x3FFFF) >> 4) + st * 1024), db = b_hi + ((((sb + SM_B) & 0x3FFFF) >> 4) + kb * (MD == 2 ? 768 : 1024));
          int nst = st + 1, nph = ph;
          if (nst == NS) { nst = 0; nph ^= 1; }
          wg_fence();
#pragma unroll
          for (int ks = 0; ks < 4; ks++) {
            if (MD == 1) {
              wgmma_n128<1, 0>(acc[0], db + ks * 128, da + ks * 16, 1);
              wgmma_n128<1, 0>(acc[1], db + 512 + ks * 128, da + ks * 16, 1);
            } else if (MD == 0) {
              wgmma_n128<0, 1>(acc[0], da + ks * 16, db + ks * 128, 1);
              wgmma_n128<0, 1>(acc[1], da + a_off + ks * 16, db + ks * 128, 1);
            } else {
              wgmma_n96<0, 1>(acc[0], da + ks * 16, db + ks * 64, 1);
              wgmma_n96<0, 1>(acc[1], da + 512 + ks * 16, db + ks * 64, 1);
            }
            if (ks == 0) {
              wg_commit();
              wg_wait<1>();
              arrive2_if(bar + B_EA + prev * 8, pd, l0 & (kb > 0), 1);
              mbar_arrive_if(bar + B_EB + eb * 8, l0 & (ec == PER) & last);
              if (ec == PER) { ec = 0; eb++; }
              ec++;
              wg_fence();
            }
            if (ks == 2) {
              if (kb == nkb - 1) { oka = false; if (type != T_QA) bar_arrive(3 + (wg ^ 1), 256); }
              else oka = mbar_try(bar + B_FA + nst * 8, nph);
              wg_fence();
            }
          }
          wg_commit();
          prev = st; st = nst; ph = nph;
        }
        wg_wait<0>();
      };
      if (type == T_V) mainloop(IntC<1>()); else if (type == T_OP || type == T_F2) mainloop(IntC<2>()); else mainloop(IntC<0>());
      arrive2_if(bar + B_EA + prev * 8, pd, l0, 1);
      mbar_arrive_if(bar + B_EB + 16, l0 & last);
      fence_regs(acc[0]); fence_regs(acc[1]);
      TR_T(tr1);
      unsigned* cnt;
      if (type <= T_V) {
        uint4* base = type == T_V ? g_Vf + (((size_t)sl * NSEG + rb * 4) * 8 + w) * 64 + lane : g_Kf + ((size_t)sl * 128 + rb * 8 + w) * 256 + lane;
        const int smb = type == T_V ? 256 : 1024, sq2 = type == T_V ? 512 : 64;
#pragma unroll
        for (int mb = 0; mb < 2; mb++) {
#pragma unroll
          for (int q = 0; q < 8; q++) {
            const float* c = &acc[mb][q * 8];
            stg128(base + mb * smb + (q >> 1) * sq2 + (q & 1) * 32, pack2(c[0], c[1]), pack2(c[2], c[3]), pack2(c[4], c[5]), pack2(c[6], c[7]));
          }
        }
        cnt = &g_kvflag[rb * 64 + type * 32 + sl];
      } else if (type == T_OP || type == T_F2) {
        uint4* base = (type == T_OP ? g_p1 : g_p2) + (((size_t)(rb * 16 + w * 2) * 18 + sl * 3) * SPL + kc) * 32 + lane;
#pragma unroll
        for (int u = 0; u < 3; u++)
#pragma unroll
          for (int mb = 0; mb < 2; mb++)
#pragma unroll
            for (int hi = 0; hi < 2; hi++) {
              const float* c = &acc[mb][u * 16 + hi * 2];
              stg128(base + ((mb * 8 + hi) * 18 + u) * (SPL * 32), pack2(c[0], c[1]), pack2(c[4], c[5]), pack2(c[8], c[9]), pack2(c[12], c[13]));
            }
        cnt = type == T_OP ? &g_cntP1[(rb) * PAD] : &g_cntP2[(rb) * PAD];
      } else if (type == T_F1) {
        uint4* base = g_gT + ((size_t)rb * 72 + sl * 2) * 1024 + w * 128 + j * 8 + g;
#pragma unroll
        for (int u = 0; u < 4; u++) {
#pragma unroll
          for (int mb = 0; mb < 2; mb++) {
#pragma unroll
            for (int hi = 0; hi < 2; hi++) {
              uint32_t p[4];
#pragma unroll
              for (int i = 0; i < 4; i++) {
                const float* c = &acc[mb][(u * 4 + i) * 4 + hi * 2];
                p[i] = pack2(gelu_tanh(c[0]), gelu_tanh(c[1]));
              }
              stg128(base + (u >> 1) * 1024 + (mb * 8 + hi) * 64 + (u & 1) * 32, p[0], p[1], p[2], p[3]);
            }
          }
        }
        cnt = &g_cntG[(rb * 8 + sl / 6) * PAD];
      } else {
        uint32_t qa[2][8][4];
#pragma unroll
        for (int mb = 0; mb < 2; mb++)
#pragma unroll
          for (int ks = 0; ks < 8; ks++)
#pragma unroll
            for (int i = 0; i < 4; i++) qa[mb][ks][i] = pack2(acc[mb][ks * 8 + 2 * i], acc[mb][ks * 8 + 2 * i + 1]);
        float sc[2][5][4];
#pragma unroll
        for (int mb = 0; mb < 2; mb++)
#pragma unroll
          for (int n = 0; n < 5; n++) { sc[mb][n][0] = sc[mb][n][1] = sc[mb][n][2] = sc[mb][n][3] = 0.f; }
        auto stg_i = [&](int e) { const int q = st + e; return q >= NS ? q - NS : q; };
        auto stg_p = [&](int e) { return st + e >= NS ? ph ^ 1 : ph; };
        const int ek = w >> 1;
        const uint32_t woff = sb + SM_A + (w & 1) * 8192 + lane * 16;
        {
          mbar_wait(bar + B_FA + stg_i(ek) * 8, stg_p(ek), t0);
          const uint32_t ka = woff + stg_i(ek) * 16384;
          uint4 kf[16];
#pragma unroll
          for (int i = 0; i < 16; i++) kf[i] = lds128(ka + i * 512);
#pragma unroll
          for (int ks = 0; ks < 8; ks++) {
#pragma unroll
            for (int mb = 0; mb < 2; mb++) {
              mma16816(sc[mb][0], qa[mb][ks], kf[ks].x, kf[ks].z);
              mma16816(sc[mb][1], qa[mb][ks], kf[ks].y, kf[ks].w);
              mma16816(sc[mb][2], qa[mb][ks], kf[8 + ks].x, kf[8 + ks].z);
              if (mb == 1) mma16816(sc[mb][3], qa[mb][ks], kf[8 + ks].y, kf[8 + ks].w);
            }
          }
          __syncwarp();
          arrive2_if(bar + B_EA + stg_i(ek) * 8, pd, l0, 2);
        }
        uint4 vf[16], km[4], vm[4];
        TR_T(tq0);
        {
          mbar_wait(bar + B_FA + stg_i(2) * 8, stg_p(2), t0);
          const uint32_t ma = sb + SM_A + stg_i(2) * 16384 + w * 2048 + lane * 16;
#pragma unroll
          for (int i = 0; i < 4; i++) km[i] = lds128(ma + i * 512);
          float s2[2][4] = {{0.f, 0.f, 0.f, 0.f}, {0.f, 0.f, 0.f, 0.f}};
#pragma unroll
          for (int u = 0; u < 4; u++) {
#pragma unroll
            for (int mb = 0; mb < 2; mb++) {
              mma16816(sc[mb][4], qa[mb][2 * u], km[u].x, km[u].y);
              mma16816(s2[mb], qa[mb][2 * u + 1], km[u].z, km[u].w);
            }
          }
#pragma unroll
          for (int mb = 0; mb < 2; mb++)
#pragma unroll
            for (int i = 0; i < 4; i++) sc[mb][4][i] += s2[mb][i];
#pragma unroll
          for (int i = 0; i < 4; i++) vm[i] = lds128(ma + 8192 + i * 512);
        }
        const float scl = 0.08838834764831845f * 1.4426950408889634f;
        const float NEG = -INFINITY;
        uint32_t pa[2][5][2];
        float inv[2][2];
#pragma unroll
        for (int mb = 0; mb < 2; mb++) {
#pragma unroll
          for (int hi = 0; hi < 2; hi++) {
            const int nd = mb + 2 * hi;
            if (2 * j > g) sc[mb][nd][hi * 2] = NEG;
            if (2 * j + 1 > g) sc[mb][nd][hi * 2 + 1] = NEG;
            float m = fmaxf(sc[mb][4][hi * 2], sc[mb][4][hi * 2 + 1]);
#pragma unroll
            for (int n = 0; n < 4; n++) if (n <= nd) m = fmaxf(m, fmaxf(sc[mb][n][hi * 2], sc[mb][n][hi * 2 + 1]));
            m = fmaxf(m, __shfl_xor_sync(~0u, m, 1)); m = fmaxf(m, __shfl_xor_sync(~0u, m, 2));
            const float mc = m * scl;
            float l = 0.f;
#pragma unroll
            for (int n = 0; n < 5; n++) {
              if (n <= nd || n == 4) {
                const float e0 = ex2(fmaf(sc[mb][n][hi * 2], scl, -mc)), e1 = ex2(fmaf(sc[mb][n][hi * 2 + 1], scl, -mc));
                l += e0 + e1;
                pa[mb][n][hi] = pack2(e0, e1);
              } else pa[mb][n][hi] = 0u;
            }
            l += __shfl_xor_sync(~0u, l, 1); l += __shfl_xor_sync(~0u, l, 2);
            inv[mb][hi] = __fdividef(1.f, l);
          }
        }
        {
          mbar_wait(bar + B_FA + stg_i(3 + ek) * 8, stg_p(3 + ek), t0);
          const uint32_t va = woff + stg_i(3 + ek) * 16384;
#pragma unroll
          for (int i = 0; i < 16; i++) vf[i] = lds128(va + i * 512);
        }
        asm volatile("" :: "r"(vm[3].w), "r"(vf[15].w) : "memory");
        __syncwarp();
        arrive2_if(bar + B_EA + stg_i(3 + ek) * 8, pd, l0, 2);
        arrive2_if(bar + B_EA + stg_i(2) * 8, pd, l0, 1);
        TR_T(tq1);
        uint32_t op[4][2][2][4];
        uint4* obase = g_oT + ((size_t)rb * 64 + sl * 2) * 1024 + w * 256 + j * 8 + g;
#pragma unroll
        for (int u = 0; u < 4; u++) {
          float o[2][4][4];
#pragma unroll
          for (int mb = 0; mb < 2; mb++) {
#pragma unroll
            for (int i = 0; i < 4; i++) {
              o[mb][i][0] = o[mb][i][1] = o[mb][i][2] = o[mb][i][3] = 0.f;
              const uint4 v0 = vf[(2 * u + (i >> 1)) * 2], v1 = vf[(2 * u + (i >> 1)) * 2 + 1];
              const uint32_t vmw = i == 0 ? vm[u].x : i == 1 ? vm[u].y : i == 2 ? vm[u].z : vm[u].w;
              mma1688(o[mb][i], pa[mb][4][0], pa[mb][4][1], vmw);
              mma16816(o[mb][i], pa[mb][0][0], pa[mb][0][1], pa[mb][1][0], pa[mb][1][1], (i & 1) ? v0.y : v0.x, (i & 1) ? v0.w : v0.z);
              if (mb == 0) mma1688(o[mb][i], pa[mb][2][0], pa[mb][2][1], (i & 1) ? v1.y : v1.x);
              else mma16816(o[mb][i], pa[mb][2][0], pa[mb][2][1], pa[mb][3][0], pa[mb][3][1], (i & 1) ? v1.y : v1.x, (i & 1) ? v1.w : v1.z);
            }
          }
          if (u == 3) bar_arrive(3 + (wg ^ 1), 256);
#pragma unroll
          for (int mb = 0; mb < 2; mb++) {
#pragma unroll
            for (int hi = 0; hi < 2; hi++) {
              const float s = inv[mb][hi];
#pragma unroll
              for (int i = 0; i < 4; i++) op[u][mb][hi][i] = pack2(o[mb][i][hi * 2] * s, o[mb][i][hi * 2 + 1] * s);
            }
          }
        }
        TR_T(tq2);
#pragma unroll
        for (int u = 0; u < 4; u++)
#pragma unroll
          for (int mb = 0; mb < 2; mb++)
#pragma unroll
            for (int hi = 0; hi < 2; hi++)
              stg128(obase + (u >> 1) * 1024 + (mb + 2 * hi) * 64 + (u & 1) * 32, op[u][mb][hi][0], op[u][mb][hi][1], op[u][mb][hi][2], op[u][mb][hi][3]);
        if (tid == wg * 128) TR_LOG(10 | (rb << 24), tq0 - tr1, tq1 - tr1);
        if (tid == wg * 128) TR_LOG(11 | (rb << 24), tq2 - tr1, tr1);
        cnt = &g_cntO[(rb * 8 + (sl < 12 ? sl / 6 : 2 + (sl - 12) / 5)) * PAD];
      }
      mbar_wait(bar + B_PE + wg * 8, ((seq >> 1) & 1) ^ 1, t0);
      if (w == 0 && l0) {
        sts64(sb + SM_PUB + wg * 8, (uint32_t)(uintptr_t)cnt, (uint32_t)((uintptr_t)cnt >> 32));
        TR_LOG(d.x, tr0, tr1);
      }
      __syncwarp();
      mbar_arrive_if(bar + B_PD + wg * 8, l0);
    }
    __syncwarp();
    asm volatile("barrier.cluster.arrive.relaxed.aligned; barrier.cluster.wait.aligned;" ::: "memory");
  }
}
}
typedef CUresult (*EncodeFn)(CUtensorMap*, CUtensorMapDataType, cuuint32_t, void*, const cuuint64_t*, const cuuint64_t*, const cuuint32_t*,
                             const cuuint32_t*, CUtensorMapInterleave, CUtensorMapSwizzle, CUtensorMapL2promotion, CUtensorMapFloatOOBfill);
static EncodeFn get_encode() {
  void* fn = nullptr; cudaDriverEntryPointQueryResult st;
  cudaGetDriverEntryPoint("cuTensorMapEncodeTiled", &fn, cudaEnableDefault, &st);
  return (EncodeFn)fn;
}
static CUtensorMap map2d(EncodeFn enc, const void* p, int rows, int cols, int brow) {
  CUtensorMap m;
  cuuint64_t dim[2] = {(cuuint64_t)cols, (cuuint64_t)rows}; cuuint64_t str[1] = {(cuuint64_t)cols * 2};
  cuuint32_t box[2] = {64, (cuuint32_t)brow}, es[2] = {1, 1};
  enc(&m, CU_TENSOR_MAP_DATA_TYPE_BFLOAT16, 2, (void*)p, dim, str, box, es, CU_TENSOR_MAP_INTERLEAVE_NONE, CU_TENSOR_MAP_SWIZZLE_128B,
      CU_TENSOR_MAP_L2_PROMOTION_L2_256B, CU_TENSOR_MAP_FLOAT_OOB_FILL_NONE);
  return m;
}
static CUtensorMap mappf(EncodeFn enc, const void* p, int rows, int cols, int bcols, int brows) {
  CUtensorMap m;
  cuuint64_t dim[2] = {(cuuint64_t)cols, (cuuint64_t)rows}; cuuint64_t str[1] = {(cuuint64_t)cols * 2};
  cuuint32_t box[2] = {(cuuint32_t)bcols, (cuuint32_t)brows}, es[2] = {1, 1};
  enc(&m, CU_TENSOR_MAP_DATA_TYPE_BFLOAT16, 2, (void*)p, dim, str, box, es, CU_TENSOR_MAP_INTERLEAVE_NONE, CU_TENSOR_MAP_SWIZZLE_NONE,
      CU_TENSOR_MAP_L2_PROMOTION_L2_128B, CU_TENSOR_MAP_FLOAT_OOB_FILL_NONE);
  return m;
}
static CUtensorMap map5d(EncodeFn enc, const void* p, int rows, int cols, int bcols) {
  CUtensorMap m;
  const cuuint64_t rs = (cuuint64_t)cols * 2;
  cuuint64_t dim[5] = {(cuuint64_t)cols, 2, 4, 4, (cuuint64_t)rows / 32}; cuuint64_t str[4] = {rs, 8 * rs, 2 * rs, 32 * rs};
  cuuint32_t box[5] = {(cuuint32_t)bcols, 2, 4, 4, 2}, es[5] = {1, 1, 1, 1, 1};
  enc(&m, CU_TENSOR_MAP_DATA_TYPE_BFLOAT16, 5, (void*)p, dim, str, box, es, CU_TENSOR_MAP_INTERLEAVE_NONE,
      bcols == 64 ? CU_TENSOR_MAP_SWIZZLE_128B : CU_TENSOR_MAP_SWIZZLE_64B,
      CU_TENSOR_MAP_L2_PROMOTION_L2_256B, CU_TENSOR_MAP_FLOAT_OOB_FILL_NONE);
  return m;
}
static CUtensorMap map3d(EncodeFn enc, const void* p) {
  CUtensorMap m;
  cuuint64_t dim[3] = {64, (cuuint64_t)DM, HD / 64}; cuuint64_t str[2] = {(cuuint64_t)HD * 2, 128};
  cuuint32_t box[3] = {64, 16, 2}, es[3] = {1, 1, 1};
  enc(&m, CU_TENSOR_MAP_DATA_TYPE_BFLOAT16, 3, (void*)p, dim, str, box, es, CU_TENSOR_MAP_INTERLEAVE_NONE, CU_TENSOR_MAP_SWIZZLE_128B,
      CU_TENSOR_MAP_L2_PROMOTION_L2_256B, CU_TENSOR_MAP_FLOAT_OOB_FILL_NONE);
  return m;
}
template <typename... KArgs, typename... Args>
static void launch(void (*k)(KArgs...), int grid, int block, int smem, cudaStream_t s, int cluster, bool pdl, Args... args) {
  cudaLaunchConfig_t cfg = {};
  cfg.gridDim = dim3(grid); cfg.blockDim = dim3(block); cfg.dynamicSmemBytes = smem; cfg.stream = s;
  cudaLaunchAttribute at[2]; int n = 0;
  if (cluster > 1) { at[n].id = cudaLaunchAttributeClusterDimension; at[n].val.clusterDim.x = cluster; at[n].val.clusterDim.y = 1; at[n].val.clusterDim.z = 1; n++; }
  if (pdl) { at[n].id = cudaLaunchAttributeProgrammaticStreamSerialization; at[n].val.programmaticStreamSerializationAllowed = 1; n++; }
  cfg.attrs = at; cfg.numAttrs = n;
  cudaLaunchKernelEx(&cfg, k, KArgs(args)...);
}
struct Ctx {
  mega::Maps maps;
  chain::Maps cmaps;
  cudaStream_t s2; cudaEvent_t evFork, evJoin;
  bool init;
};
static void setup(Ctx& c, void* const* d_in) {
  EncodeFn enc = get_encode();
  c.maps.m[mega::T_K] = map2d(enc, d_in[3], DM, HD, 64); c.maps.m[mega::T_V] = map2d(enc, d_in[4], DM, HD, 64);
  c.maps.m[mega::T_QA] = map2d(enc, d_in[2], DM, HD, 64);
  c.maps.m[mega::T_OP] = map5d(enc, d_in[5], HD, DM, 32); c.maps.m[mega::T_F1] = map5d(enc, d_in[8], DM, FF, 64); c.maps.m[mega::T_F2] = map5d(enc, d_in[10], FF, DM, 32);
  c.maps.pf[0] = mappf(enc, d_in[2], DM, HD, 128, 192); c.maps.pf[1] = mappf(enc, d_in[5], HD, DM, 96, 256);
  c.maps.pf[2] = mappf(enc, d_in[8], DM, FF, 128, 192); c.maps.pf[3] = mappf(enc, d_in[10], FF, DM, 96, 256);
  c.cmaps.q = map3d(enc, d_in[2]); c.cmaps.k = map3d(enc, d_in[3]); c.cmaps.v = map3d(enc, d_in[4]); c.cmaps.o = map2d(enc, d_in[5], HD, DM, 128);
  cudaFuncSetAttribute(chain::chain_kernel, cudaFuncAttributeNonPortableClusterSizeAllowed, 1);
  cudaFuncSetAttribute(chain::chain_kernel, cudaFuncAttributeMaxDynamicSharedMemorySize, chain::SM_TOTAL);
  cudaFuncSetAttribute(mega::mega_kernel, cudaFuncAttributeMaxDynamicSharedMemorySize, mega::SM_TOTAL);
  cudaFuncAttributes fa;
  cudaFuncGetAttributes(&fa, gate_kernel);
  int lo, hi; cudaDeviceGetStreamPriorityRange(&lo, &hi);
  cudaStreamCreateWithPriority(&c.s2, cudaStreamNonBlocking, hi);
  cudaEventCreateWithFlags(&c.evFork, cudaEventDisableTiming); cudaEventCreateWithFlags(&c.evJoin, cudaEventDisableTiming);
  c.init = true;
}
#define NCH 64
static Ctx g_ctx;
extern "C" void kernel_launch(void* const* d_in, const int* in_sizes, int n_in, void* d_out, int out_size) {
  Ctx& c = g_ctx;
  if (!c.init) setup(c, d_in);
  const bf16 *x = (const bf16*)d_in[0], *mem0 = (const bf16*)d_in[1], *b1 = (const bf16*)d_in[9], *b2 = (const bf16*)d_in[11];
  bf16* out = (bf16*)d_out;
  cudaStream_t s = cudaStreamPerThread;
  cudaEventRecord(c.evFork, s);
  cudaStreamWaitEvent(c.s2, c.evFork, 0);
  launch(chain::chain_kernel, NCH, chain::NTHREADS, chain::SM_TOTAL, c.s2, 16, false, c.cmaps, mem0, x, (const bf16*)d_in[2], (const bf16*)d_in[3], (const bf16*)d_in[4], (const bf16*)d_in[5], 0u);
  cudaEventRecord(c.evJoin, c.s2);
  launch(gate_kernel, 1, 1, 0, s, 1, false);
  launch(mega::mega_kernel, 132, 384, mega::SM_TOTAL, s, 2, true, c.maps, x, b1, b2, out);
  cudaStreamWaitEvent(s, c.evJoin, 0);
}
```

```cpp
#include <cuda_runtime.h>
#include <cuda_bf16.h>
#include <cuda.h>
#include <stdint.h>

typedef __nv_bfloat16 bf16;

constexpr int SEQ = 2048, DM = 576, NH = 32, DH = 128, HD = 4096, FF = 4608, NSEG = 64, NRB = 16;

__device__ __align__(1024) uint4 g_Kf[NH * 256 * 4 * 32];
__device__ __align__(1024) uint4 g_Vf[NH * NSEG * 128 * 4];
__device__ __align__(1024) uint4 g_Kmf[NH * NSEG * 4 * 32];
__device__ __align__(1024) uint4 g_Vmf[NH * NSEG * 4 * 32];
__device__ __align__(8192) uint4 g_xch[64 * 512];
__device__ unsigned g_kvflag[NRB * 64];
__device__ unsigned g_memflag[NH * 8];
__device__ __align__(1024) uint4 g_xnT[NRB * 9 * 1024];
__device__ unsigned g_cntX[NRB * 32];
__device__ unsigned g_prog;
__device__ unsigned g_epoch;
__device__ unsigned g_resident;
__device__ unsigned g_err;

__device__ __forceinline__ uint32_t smem_u32(const void* p) { return (uint32_t)__cvta_generic_to_shared(p); }
__device__ __forceinline__ void mbar_init(uint32_t a, int cnt) { asm volatile("mbarrier.init.shared::cta.b64 [%0], %1;" :: "r"(a), "r"(cnt) : "memory"); }
__device__ __forceinline__ void mbar_expect(uint32_t a, int bytes) { asm volatile("mbarrier.arrive.expect_tx.shared::cta.b64 _, [%0], %1;" :: "r"(a), "r"(bytes) : "memory"); }
__device__ __forceinline__ void mbar_arrive(uint32_t a) { asm volatile("mbarrier.arrive.shared::cta.b64 _, [%0];" :: "r"(a) : "memory"); }
__device__ __forceinline__ void mbar_arrive_if(uint32_t a, int p) { asm volatile("{ .reg .pred q; setp.ne.b32 q, %1, 0; @q mbarrier.arrive.shared::cta.b64 _, [%0]; }" :: "r"(a), "r"(p) : "memory"); }
__device__ __forceinline__ bool mbar_try(uint32_t a, uint32_t parity) {
  uint32_t ok;
  asm volatile("{ .reg .pred p; mbarrier.try_wait.parity.shared::cta.b64 p, [%1], %2; selp.u32 %0, 1, 0, p; }" : "=r"(ok) : "r"(a), "r"(parity) : "memory");
  return ok;
}
__device__ __forceinline__ bool mbar_test(uint32_t a, uint32_t parity) {
  uint32_t ok;
  asm volatile("{ .reg .pred p; mbarrier.test_wait.parity.shared::cta.b64 p, [%1], %2; selp.u32 %0, 1, 0, p; }" : "=r"(ok) : "r"(a), "r"(parity) : "memory");
  return ok;
}
__device__ __forceinline__ bool mbar_try_cl(uint32_t a, uint32_t parity) {
  uint32_t ok;
  asm volatile("{ .reg .pred p; mbarrier.try_wait.parity.acquire.cluster.shared::cta.b64 p, [%1], %2; selp.u32 %0, 1, 0, p; }" : "=r"(ok) : "r"(a), "r"(parity) : "memory");
  return ok;
}
__device__ __forceinline__ uint32_t clk32() { uint32_t c; asm volatile("mov.u32 %0, %%clock;" : "=r"(c)); return c; }
constexpr uint32_t TIMEOUT_CLKS = 400000000u;
__device__ __forceinline__ bool timed_out(uint32_t t0) {
  if (clk32() - t0 > TIMEOUT_CLKS) { g_err = 1; return true; }
  return false;
}
__device__ __forceinline__ void mbar_wait(uint32_t a, uint32_t parity, uint32_t t0) {
  if (mbar_try(a, parity)) return;
  while (!mbar_try(a, parity)) { if (timed_out(t0)) break; }
}
__device__ __forceinline__ void mbar_wait_cl(uint32_t a, uint32_t parity, uint32_t t0) {
  while (!mbar_try_cl(a, parity)) { if (timed_out(t0)) break; }
}
__device__ __forceinline__ uint32_t mapa(uint32_t a, uint32_t r) { uint32_t d; asm volatile("mapa.shared::cluster.u32 %0, %1, %2;" : "=r"(d) : "r"(a), "r"(r)); return d; }
__device__ __forceinline__ void st_async16(uint32_t a, uint32_t x, uint32_t y, uint32_t z, uint32_t w, uint32_t bar) {
  asm volatile("st.async.shared::cluster.mbarrier::complete_tx::bytes.v4.b32 [%0], {%1,%2,%3,%4}, [%5];" :: "r"(a), "r"(x), "r"(y), "r"(z), "r"(w), "r"(bar) : "memory");
}
__device__ __forceinline__ void st_async8(uint32_t a, uint32_t x, uint32_t y, uint32_t bar) {
  asm volatile("st.async.shared::cluster.mbarrier::complete_tx::bytes.v2.b32 [%0], {%1,%2}, [%3];" :: "r"(a), "r"(x), "r"(y), "r"(bar) : "memory");
}
__device__ __forceinline__ void bar_sync(int id, int n) { asm volatile("bar.sync %0, %1;" :: "r"(id), "r"(n) : "memory"); }
__device__ __forceinline__ void bar_arrive(int id, int n) { asm volatile("bar.arrive %0, %1;" :: "r"(id), "r"(n) : "memory"); }
__device__ __forceinline__ void cluster_sync() { asm volatile("barrier.cluster.arrive.release.aligned; barrier.cluster.wait.acquire.aligned;" ::: "memory"); }
__device__ __forceinline__ uint32_t pack2(float lo, float hi) { uint32_t d; asm("cvt.rn.bf16x2.f32 %0, %1, %2;" : "=r"(d) : "f"(hi), "f"(lo)); return d; }
__device__ __forceinline__ float bflo(uint32_t v) { return __uint_as_float(v << 16); }
__device__ __forceinline__ float bfhi(uint32_t v) { return __uint_as_float(v & 0xffff0000u); }
__device__ __forceinline__ uint32_t movmat(uint32_t a) { uint32_t d; asm volatile("movmatrix.sync.aligned.m8n8.trans.b16 %0, %1;" : "=r"(d) : "r"(a)); return d; }
__device__ __forceinline__ uint32_t hadd2bf(uint32_t a, uint32_t b) { uint32_t d; asm("add.rn.bf16x2 %0, %1, %2;" : "=r"(d) : "r"(a), "r"(b)); return d; }
__device__ __forceinline__ void mma16816(float (&c)[4], uint32_t a0, uint32_t a1, uint32_t a2, uint32_t a3, uint32_t b0, uint32_t b1) {
  asm volatile("mma.sync.aligned.m16n8k16.row.col.f32.bf16.bf16.f32 {%0,%1,%2,%3}, {%4,%5,%6,%7}, {%8,%9}, {%0,%1,%2,%3};"
    : "+f"(c[0]), "+f"(c[1]), "+f"(c[2]), "+f"(c[3]) : "r"(a0), "r"(a1), "r"(a2), "r"(a3), "r"(b0), "r"(b1));
}
__device__ __forceinline__ void mma16816(float (&c)[4], const uint32_t (&a)[4], uint32_t b0, uint32_t b1) { mma16816(c, a[0], a[1], a[2], a[3], b0, b1); }
__device__ __forceinline__ void mma1688(float (&c)[4], uint32_t a0, uint32_t a1, uint32_t b0) {
  asm volatile("mma.sync.aligned.m16n8k8.row.col.f32.bf16.bf16.f32 {%0,%1,%2,%3}, {%4,%5}, {%6}, {%0,%1,%2,%3};"
    : "+f"(c[0]), "+f"(c[1]), "+f"(c[2]), "+f"(c[3]) : "r"(a0), "r"(a1), "r"(b0));
}
__device__ __forceinline__ void ldsm4t(uint32_t (&r)[4], uint32_t a) {
  asm volatile("ldmatrix.sync.aligned.m8n8.x4.trans.shared.b16 {%0,%1,%2,%3}, [%4];" : "=r"(r[0]), "=r"(r[1]), "=r"(r[2]), "=r"(r[3]) : "r"(a) : "memory");
}
__device__ __forceinline__ uint4 lds128(uint32_t a) { uint4 v; asm volatile("ld.shared.v4.b32 {%0,%1,%2,%3}, [%4];" : "=r"(v.x), "=r"(v.y), "=r"(v.z), "=r"(v.w) : "r"(a) : "memory"); return v; }
__device__ __forceinline__ uint2 lds64(uint32_t a) { uint2 v; asm volatile("ld.shared.v2.b32 {%0,%1}, [%2];" : "=r"(v.x), "=r"(v.y) : "r"(a) : "memory"); return v; }
__device__ __forceinline__ void sts128(uint32_t a, uint32_t x, uint32_t y, uint32_t z, uint32_t w) { asm volatile("st.shared.v4.b32 [%0], {%1,%2,%3,%4};" :: "r"(a), "r"(x), "r"(y), "r"(z), "r"(w) : "memory"); }
__device__ __forceinline__ void sts64(uint32_t a, uint32_t x, uint32_t y) { asm volatile("st.shared.v2.b32 [%0], {%1,%2};" :: "r"(a), "r"(x), "r"(y) : "memory"); }
__device__ __forceinline__ void sts32(uint32_t a, uint32_t x) { asm volatile("st.shared.b32 [%0], %1;" :: "r"(a), "r"(x) : "memory"); }
__device__ __forceinline__ void cp_async16(uint32_t dst, const void* src) { asm volatile("cp.async.cg.shared.global [%0], [%1], 16;" :: "r"(dst), "l"(src) : "memory"); }
__device__ __forceinline__ void cp_async_wait_all() { asm volatile("cp.async.wait_all;" ::: "memory"); }
__device__ __forceinline__ uint4 ldg_cg(const void* p) { uint4 v; asm volatile("ld.global.cg.v4.b32 {%0,%1,%2,%3}, [%4];" : "=r"(v.x), "=r"(v.y), "=r"(v.z), "=r"(v.w) : "l"(p) : "memory"); return v; }
__device__ __forceinline__ uint4 ld_relaxed16(const void* p) { uint4 v; asm volatile("ld.relaxed.gpu.global.v4.b32 {%0,%1,%2,%3}, [%4];" : "=r"(v.x), "=r"(v.y), "=r"(v.z), "=r"(v.w) : "l"(p) : "memory"); return v; }
__device__ __forceinline__ void st_relaxed16(void* p, uint32_t x, uint32_t y, uint32_t z, uint32_t w) { asm volatile("st.relaxed.gpu.global.v4.b32 [%0], {%1,%2,%3,%4};" :: "l"(p), "r"(x), "r"(y), "r"(z), "r"(w) : "memory"); }
__device__ __forceinline__ unsigned ld_acquire(const unsigned* p) { unsigned v; asm volatile("ld.acquire.gpu.global.u32 %0, [%1];" : "=r"(v) : "l"(p) : "memory"); return v; }
__device__ __forceinline__ uint32_t ldg32(const void* p) { uint32_t v; asm volatile("ld.global.nc.b32 %0, [%1];" : "=r"(v) : "l"(p)); return v; }
__device__ __forceinline__ unsigned ld_relaxed(const unsigned* p) { unsigned v; asm volatile("ld.relaxed.gpu.global.u32 %0, [%1];" : "=r"(v) : "l"(p) : "memory"); return v; }
__device__ __forceinline__ void st_release(unsigned* p, unsigned v) { asm volatile("st.release.gpu.global.u32 [%0], %1;" :: "l"(p), "r"(v) : "memory"); }
__device__ __forceinline__ float ex2(float x) { float y; asm("ex2.approx.ftz.f32 %0, %1;" : "=f"(y) : "f"(x)); return y; }

__device__ __forceinline__ void st_b128(void* p, uint32_t x, uint32_t y, uint32_t z, uint32_t w) {
  asm volatile("{ .reg .b128 t; .reg .b64 lo, hi; mov.b64 lo, {%1,%2}; mov.b64 hi, {%3,%4}; mov.b128 t, {lo,hi}; st.relaxed.gpu.global.b128 [%0], t; }"
    :: "l"(p), "r"(x), "r"(y), "r"(z), "r"(w) : "memory");
}
__device__ __forceinline__ uint4 ld_b128(const void* p) {
  uint4 v;
  asm volatile("{ .reg .b128 t; .reg .b64 lo, hi; ld.relaxed.gpu.global.b128 t, [%4]; mov.b128 {lo,hi}, t; mov.b64 {%0,%1}, lo; mov.b64 {%2,%3}, hi; }"
    : "=r"(v.x), "=r"(v.y), "=r"(v.z), "=r"(v.w) : "l"(p) : "memory");
  return v;
}
__device__ __forceinline__ void wg_fence() { asm volatile("wgmma.fence.sync.aligned;" ::: "memory"); }
__device__ __forceinline__ void wg_commit() { asm volatile("wgmma.commit_group.sync.aligned;" ::: "memory"); }
template <int N> __device__ __forceinline__ void wg_wait() { asm volatile("wgmma.wait_group.sync.aligned %0;" :: "n"(N) : "memory"); }
__device__ __forceinline__ uint64_t make_desc(uint32_t addr, uint32_t lbo, uint32_t sbo, uint32_t mode) {
  return (uint64_t)((addr & 0x3FFFF) >> 4) | ((uint64_t)(lbo >> 4) << 16) | ((uint64_t)(sbo >> 4) << 32) | ((uint64_t)mode << 62);
}
__device__ __forceinline__ void tma2d(uint32_t dst, const CUtensorMap* m, int c0, int c1, uint32_t bar) {
  asm volatile("cp.async.bulk.tensor.2d.shared::cluster.global.mbarrier::complete_tx::bytes [%0], [%1, {%3, %4}], [%2];"
    :: "r"(dst), "l"(m), "r"(bar), "r"(c0), "r"(c1) : "memory");
}
__device__ __forceinline__ bool elect() {
  uint32_t p; asm volatile("{ .reg .pred q; elect.sync _|q, 0xffffffff; selp.u32 %0, 1, 0, q; }" : "=r"(p)); return p;
}
__device__ __forceinline__ void tma3d(uint32_t dst, const CUtensorMap* m, int c1, int c2, uint32_t bar) {
  asm volatile("cp.async.bulk.tensor.3d.shared::cluster.global.mbarrier::complete_tx::bytes [%0], [%1, {%5, %3, %4}], [%2];"
    :: "r"(dst), "l"(m), "r"(bar), "r"(c1), "r"(c2), "r"(0) : "memory");
}
__device__ __forceinline__ void tma5d(uint32_t dst, const CUtensorMap* m, int c0, int c4, uint32_t bar) {
  asm volatile("cp.async.bulk.tensor.5d.shared::cluster.global.mbarrier::complete_tx::bytes [%0], [%1, {%3, %5, %5, %5, %4}], [%2];"
    :: "r"(dst), "l"(m), "r"(bar), "r"(c0), "r"(c4), "r"(0) : "memory");
}
__device__ __forceinline__ void bulk_g2s(uint32_t dst, const void* src, uint32_t bytes, uint32_t bar) {
  asm volatile("cp.async.bulk.shared::cluster.global.mbarrier::complete_tx::bytes [%0], [%1], %2, [%3];" :: "r"(dst), "l"(src), "r"(bytes), "r"(bar) : "memory");
}
__device__ __forceinline__ void stg128(void* p, uint32_t x, uint32_t y, uint32_t z, uint32_t w) {
  asm volatile("st.global.v4.b32 [%0], {%1,%2,%3,%4};" :: "l"(p), "r"(x), "r"(y), "r"(z), "r"(w) : "memory");
}
template <int N> __device__ __forceinline__ void fence_regs(float (&d)[N]) {
#pragma unroll
  for (int i = 0; i < N; i++) asm volatile("" : "+f"(d[i]) :: "memory");
}

#define TR_T(v)
#define TR_VAR(v)
#define TR_SET(v)
#define TR_LOG(info, a, b)
template <int TA, int TB>
__device__ __forceinline__ void wgmma_n96(float (&d)[64], uint64_t da, uint64_t db, int scale_d) {
  asm volatile("{ .reg .pred p; setp.ne.b32 p, %50, 0;\n"
    "wgmma.mma_async.sync.aligned.m64n96k16.f32.bf16.bf16 {%0, %1, %2, %3, %4, %5, %6, %7, %8, %9, %10, %11, %12, %13, %14, %15, %16, %17, %18, %19, %20, %21, %22, %23, %24, %25, %26, %27, %28, %29, %30, %31, %32, %33, %34, %35, %36, %37, %38, %39, %40, %41, %42, %43, %44, %45, %46, %47}, %48, %49, p, 1, 1, %51, %52; }"
    : "+f"(d[0]), "+f"(d[1]), "+f"(d[2]), "+f"(d[3]), "+f"(d[4]), "+f"(d[5]), "+f"(d[6]), "+f"(d[7]), "+f"(d[8]), "+f"(d[9]), "+f"(d[10]), "+f"(d[11]), "+f"(d[12]), "+f"(d[13]), "+f"(d[14]), "+f"(d[15]), "+f"(d[16]), "+f"(d[17]), "+f"(d[18]), "+f"(d[19]), "+f"(d[20]), "+f"(d[21]), "+f"(d[22]), "+f"(d[23]), "+f"(d[24]), "+f"(d[25]), "+f"(d[26]), "+f"(d[27]), "+f"(d[28]), "+f"(d[29]), "+f"(d[30]), "+f"(d[31]), "+f"(d[32]), "+f"(d[33]), "+f"(d[34]), "+f"(d[35]), "+f"(d[36]), "+f"(d[37]), "+f"(d[38]), "+f"(d[39]), "+f"(d[40]), "+f"(d[41]), "+f"(d[42]), "+f"(d[43]), "+f"(d[44]), "+f"(d[45]), "+f"(d[46]), "+f"(d[47])
    : "l"(da), "l"(db), "r"(scale_d), "n"(TA), "n"(TB));
}
template <int TA, int TB>
__device__ __forceinline__ void wgmma_n128(float (&d)[64], uint64_t da, uint64_t db, int scale_d) {
  asm volatile("{ .reg .pred p; setp.ne.b32 p, %66, 0;\n"
    "wgmma.mma_async.sync.aligned.m64n128k16.f32.bf16.bf16 {%0, %1, %2, %3, %4, %5, %6, %7, %8, %9, %10, %11, %12, %13, %14, %15, %16, %17, %18, %19, %20, %21, %22, %23, %24, %25, %26, %27, %28, %29, %30, %31, %32, %33, %34, %35, %36, %37, %38, %39, %40, %41, %42, %43, %44, %45, %46, %47, %48, %49, %50, %51, %52, %53, %54, %55, %56, %57, %58, %59, %60, %61, %62, %63}, %64, %65, p, 1, 1, %67, %68; }"
    : "+f"(d[0]), "+f"(d[1]), "+f"(d[2]), "+f"(d[3]), "+f"(d[4]), "+f"(d[5]), "+f"(d[6]), "+f"(d[7]), "+f"(d[8]), "+f"(d[9]), "+f"(d[10]), "+f"(d[11]), "+f"(d[12]), "+f"(d[13]), "+f"(d[14]), "+f"(d[15]), "+f"(d[16]), "+f"(d[17]), "+f"(d[18]), "+f"(d[19]), "+f"(d[20]), "+f"(d[21]), "+f"(d[22]), "+f"(d[23]), "+f"(d[24]), "+f"(d[25]), "+f"(d[26]), "+f"(d[27]), "+f"(d[28]), "+f"(d[29]), "+f"(d[30]), "+f"(d[31]), "+f"(d[32]), "+f"(d[33]), "+f"(d[34]), "+f"(d[35]), "+f"(d[36]), "+f"(d[37]), "+f"(d[38]), "+f"(d[39]), "+f"(d[40]), "+f"(d[41]), "+f"(d[42]), "+f"(d[43]), "+f"(d[44]), "+f"(d[45]), "+f"(d[46]), "+f"(d[47]), "+f"(d[48]), "+f"(d[49]), "+f"(d[50]), "+f"(d[51]), "+f"(d[52]), "+f"(d[53]), "+f"(d[54]), "+f"(d[55]), "+f"(d[56]), "+f"(d[57]), "+f"(d[58]), "+f"(d[59]), "+f"(d[60]), "+f"(d[61]), "+f"(d[62]), "+f"(d[63])
    : "l"(da), "l"(db), "r"(scale_d), "n"(TA), "n"(TB));
}
#define POLL_MODE 1
#define STAGGER 0
#define WEARLY 6
#define WLATE 1
#define PREF 0
#define CREG 216
#define AREG 72
#define KEEPALIVE 150
#define OWNMMA 0
#define WXE 4
#define PREF_M0 2
#define POLL_REP 2
namespace chain {
constexpr int SLOT = 4096;
constexpr int NX = 8;
constexpr int NPV = 9;
constexpr int NV2 = 18 - NPV;
constexpr int NPERM = 2 * (18 - NX) + NPV;
constexpr int SM_X = 0;
constexpr int SM_V2 = SM_X + 2 * NX * SLOT;
constexpr int SM_KX = SM_V2 + NV2 * SLOT;
constexpr int SM_VX = SM_KX + 8192;
constexpr int SM_WO = SM_VX + 8192;
static_assert(SM_WO == NPERM * SLOT, "staging area = X + V2 + KX + VX");
constexpr int SM_MEM = SM_WO + 5 * 16384;
constexpr int SM_OQK = SM_MEM + 9 * 512;
constexpr int SM_XQK = SM_OQK + 4096;
constexpr int SM_OV = SM_XQK + 4096;
constexpr int SM_XV = SM_OV + 2048;
constexpr int SM_S = SM_XV + 2048;
constexpr int SM_O = SM_S + 1536;
constexpr int SM_RS = SM_O + 2048;
constexpr int SM_MB = SM_RS + 8 * 576;
constexpr int SM_INV = SM_MB + 3 * 1152;
constexpr int SM_BAR = SM_INV + 128;
constexpr int SM_PROF = SM_BAR + 128;
constexpr int SM_TOTAL = SM_PROF + 256;
static_assert(SM_TOTAL <= 232448, "smem");
constexpr int B_AG = 0  , B_XQK = 40, B_XV = 48, B_RS = 56, B_KV = 64, B_L = 72, B_W = 80  ;
constexpr int RS_BYTES = 7 * 512 + 8 * 64;
constexpr int BAR_OQK = 1, BAR_S = 2, BAR_O = 3, BAR_ALL = 4, BAR_KVF = 5, BAR_AB = 6, BAR_AB2 = 7, BAR_C = 8;
constexpr int NTHREADS = 384;
constexpr int REG_C = CREG, REG_A = AREG;
static_assert(2 * REG_C + REG_A <= 504, "register pool");

#define PROF(slot) do {} while (0)
#define PROFN(slot) do {} while (0)
#define PROFS() do {} while (0)
#define PROF0(slot) do {} while (0)
#define PROF1(slot) do {} while (0)

struct Maps { CUtensorMap q, k, v, o; };

__device__ __forceinline__ void mmaq(float (&c)[4], const uint4& a, uint32_t b0, uint32_t b1) { mma16816(c, a.x, a.y, a.z, a.w, b0, b1); }
__device__ __forceinline__ int opaque(int v) { int d; asm volatile("mov.u32 %0, %1;" : "=r"(d) : "r"(v)); return d; }
__device__ __forceinline__ uint32_t dep(uint32_t base, uint32_t v, uint32_t zero) {
  uint32_t d; asm("lop3.b32 %0, %1, %2, %3, 0xF8;" : "=r"(d) : "r"(base), "r"(v), "r"(zero)); return d;
}
__device__ __forceinline__ uint32_t frag_off(int lane, int cp) {
  const int mat = lane >> 3, r = lane & 7;
  return ((mat >> 1) * 8 + r) * 128 + (((cp * 2 + (mat & 1)) ^ r) * 16);
}

template <bool EXTRA>
__device__ __forceinline__ void softmax_pv(int s, int x, uint32_t sb, uint32_t sl, uint32_t bar, int lane_in, int a, int head, uint32_t t0,
                                           uint32_t (&WX)[8][4], uint4& vm_out, int P) {
  const int lane = opaque(lane_in);
  uint4* const vm_ptr = g_Vmf + (size_t)head * NSEG * 128 + x * 32 + lane;
  const float sc = 0.08838834764831845f * 1.4426950408889634f;
  const uint32_t wa = sb + SM_WO + 4 * 16384 + frag_off(lane, x);
  bar_sync(BAR_S, 128);
  const uint4 s0 = lds128(sl + SM_S), s1 = lds128(sl + SM_S + 512), s2 = lds128(sl + SM_S + 1024);
  uint4 vx[4];
#pragma unroll
  for (int u = 0; u < 4; u++) vx[u] = lds128(sl + SM_VX + x * 2048 + u * 512);
  const bool okv = mbar_try(bar + B_XV, s & 1);
  const uint32_t lv = sb + x * 512 + lane * 8;
  float y[10] = {__uint_as_float(s0.x), __uint_as_float(s0.y), __uint_as_float(s0.z), __uint_as_float(s0.w),
                 __uint_as_float(s1.x), __uint_as_float(s1.y), __uint_as_float(s1.z), __uint_as_float(s1.w),
                 __uint_as_float(s2.x) + __uint_as_float(s2.z), __uint_as_float(s2.y) + __uint_as_float(s2.w)};
  float m = fmaxf(fmaxf(fmaxf(y[0], y[1]), fmaxf(y[2], y[3])), fmaxf(fmaxf(y[4], y[5]), fmaxf(y[6], y[7])));
  m = fmaxf(m, fmaxf(y[8], y[9]));
  if (P) PROF(12);
  m = fmaxf(m, __shfl_xor_sync(0xffffffffu, m, 1));
  m = fmaxf(m, __shfl_xor_sync(0xffffffffu, m, 2));
  if (!okv) mbar_wait(bar + B_XV, s & 1, t0);
  const uint2 ov0 = lds64(lv + SM_OV), xv0 = lds64(lv + SM_XV), ov1 = lds64(lv + SM_OV + 256), xv1 = lds64(lv + SM_XV + 256);
  if (EXTRA) {
#pragma unroll
    for (int u = 0; u < WXE; u++) ldsm4t(WX[u], wa + u * 2048);
  }
  const float mc = m * sc;
#pragma unroll
  for (int i = 0; i < 10; i++) y[i] = ex2(fmaf(y[i], sc, -mc));
  const uint32_t p0 = pack2(y[0], y[1]), p1 = pack2(y[2], y[3]), p2 = pack2(y[4], y[5]), p3 = pack2(y[6], y[7]), p4 = pack2(y[8], y[9]);
  const uint4 vm = make_uint4(hadd2bf(ov0.x, xv0.x), hadd2bf(ov0.y, xv0.y), hadd2bf(ov1.x, xv1.x), hadd2bf(ov1.y, xv1.y));
  float o0[4] = {0.f, 0.f, 0.f, 0.f}, o1[4] = {0.f, 0.f, 0.f, 0.f}, o2[4] = {0.f, 0.f, 0.f, 0.f}, o3[4] = {0.f, 0.f, 0.f, 0.f};
  mmaq(o0, vx[0], p0, p1); mmaq(o2, vx[2], p0, p1);
  mmaq(o0, vx[1], p2, p3); mmaq(o2, vx[3], p2, p3);
  mma1688(o1, vm.x, vm.y, p4); mma1688(o3, vm.z, vm.w, p4);
  asm volatile("stmatrix.sync.aligned.m8n8.x4.shared.b16 [%0], {%1,%2,%3,%4};" :: "r"(sl + SM_O + x * 512),
    "r"(pack2(o0[0] + o1[0], o0[1] + o1[1])), "r"(pack2(o0[2] + o1[2], o0[3] + o1[3])),
    "r"(pack2(o2[0] + o3[0], o2[1] + o3[1])), "r"(pack2(o2[2] + o3[2], o2[3] + o3[3])) : "memory");
  if (P) PROF(13);
  bar_arrive(BAR_O, NTHREADS);
  if (x != 3) bar_arrive(BAR_KVF, 128);
  if (EXTRA) {
#pragma unroll
    for (int u = WXE; u < 8; u++) ldsm4t(WX[u], wa + u * 2048);
    bar_sync(BAR_AB2, 128);
  } else {
    bar_arrive(BAR_AB2, 128);
    if (x == 3) {
      float l = ((y[0] + y[1]) + (y[2] + y[3])) + ((y[4] + y[5]) + (y[6] + y[7])) + (y[8] + y[9]);
      l += __shfl_xor_sync(0xffffffffu, l, 1);
      l += __shfl_xor_sync(0xffffffffu, l, 2);
      float inv; asm("rcp.approx.ftz.f32 %0, %1;" : "=f"(inv) : "f"(l));
      if ((lane & 3) == 0) sts32(sb + SM_INV + lane, __float_as_uint(inv));
      __syncwarp();
      mbar_arrive_if(bar + B_L, lane == 0 && s >= 0);
      bar_sync(BAR_KVF, 128);
    }
  }
  if (!EXTRA) { if (a == 0 && s >= 0) vm_ptr[(size_t)s * 128] = vm; } else vm_out = vm;
}

__device__ __forceinline__ void reduce_exchange(int x, int gi, int a, int s, uint32_t sb, uint32_t bar, int lane_in, uint32_t t0, int P, int bid) {
  const int lane = opaque(lane_in);
  const int tt = x * 32 + lane;
  const bool act = tt < 72;
  const int hc = lane & 1;
  const uint32_t rs_addr = sb + SM_RS + tt * 8;
  const uint32_t mem_addr = sb + SM_MEM + (x < 2 ? (tt >> 1) * 16 : 8 * 512 + (4 * gi + (lane >> 1)) * 16);
  const uint32_t mem_step = x < 2 ? 512 : 0;
  const uint32_t ma = mem_addr + (1 + hc) * mem_step;
  const uint32_t r0 = 2 * ((gi - 1 - hc) & 7) + a, r1 = 2 * ((gi - 3 - hc) & 7) + a, r2 = 2 * ((gi - 5 - hc) & 7) + a, r3 = 2 * ((gi - 7) & 7) + a;
  const uint32_t d0 = mapa(ma, r0), e0 = mapa(bar + B_AG + (x < 2 ? 8 : 32), r0);
  const uint32_t d1 = mapa(ma + 2 * mem_step, r1), e1_ = mapa(bar + B_AG + (x < 2 ? 16 : 32), r1);
  const uint32_t d2 = mapa(ma + 4 * mem_step, r2), e2_ = mapa(bar + B_AG + (x < 2 ? 24 : 32), r2);
  const uint32_t d3 = mapa(ma + 6 * mem_step, r3), e3_ = mapa(bar + B_AG + 32, r3);
  char* const xb = reinterpret_cast<char*>(g_xch) + (tt * 16 + (s & 1) * 2048);
  void* const xw = xb + (size_t)bid * 8192;
  const void* const xr1 = xb + (size_t)(bid ^ 16) * 8192;
  const void* const xr2 = xb + (size_t)(bid ^ 32) * 8192;
  const void* const xr3 = xb + (size_t)(bid ^ 48) * 8192;
  const uint32_t tag = (s + 1) & 15;
  mbar_wait(bar + B_RS, s & 1, t0);
  if (P) PROF(20);
  uint32_t w0 = 0, w1 = 0;
  if (act) {
    uint2 r[8];
#pragma unroll
    for (int u = 0; u < 8; u++) r[u] = lds64(rs_addr + u * 576);
    float f0 = ((bflo(r[0].x) + bflo(r[1].x)) + (bflo(r[2].x) + bflo(r[3].x))) + ((bflo(r[4].x) + bflo(r[5].x)) + (bflo(r[6].x) + bflo(r[7].x)));
    float f1 = ((bfhi(r[0].x) + bfhi(r[1].x)) + (bfhi(r[2].x) + bfhi(r[3].x))) + ((bfhi(r[4].x) + bfhi(r[5].x)) + (bfhi(r[6].x) + bfhi(r[7].x)));
    float f2 = ((bflo(r[0].y) + bflo(r[1].y)) + (bflo(r[2].y) + bflo(r[3].y))) + ((bflo(r[4].y) + bflo(r[5].y)) + (bflo(r[6].y) + bflo(r[7].y)));
    float f3 = ((bfhi(r[0].y) + bfhi(r[1].y)) + (bfhi(r[2].y) + bfhi(r[3].y))) + ((bfhi(r[4].y) + bfhi(r[5].y)) + (bfhi(r[6].y) + bfhi(r[7].y)));
    const uint32_t m0 = (__float_as_uint(f0) & ~15u) | tag;
    if (s >= 0) st_b128(xw, m0, __float_as_uint(f1), __float_as_uint(f2), __float_as_uint(f3));
    if (P) PROF(21);
    uint4 e1, e2, e3;
    const uint32_t mb = sb + SM_MB + tt * 16;
    while (true) {
      cp_async16(mb, xr1); cp_async16(mb + 1152, xr2); cp_async16(mb + 2304, xr3);
      bool ok = false;
#pragma unroll
      for (int i = 0; i < POLL_REP; i++) {
        e1 = lds128(mb); e2 = lds128(mb + 1152); e3 = lds128(mb + 2304);
        ok = (((e1.x ^ tag) | (e2.x ^ tag) | (e3.x ^ tag)) & 15u) == 0;
        if (ok) break;
      }
      if (ok || s < 0 || timed_out(t0)) break;
    }
    if (P) PROF(22);
    f0 = (__uint_as_float(m0) + __uint_as_float(e1.x)) + (__uint_as_float(e2.x) + __uint_as_float(e3.x));
    f1 = (f1 + __uint_as_float(e1.y)) + (__uint_as_float(e2.y) + __uint_as_float(e3.y));
    f2 = (f2 + __uint_as_float(e1.z)) + (__uint_as_float(e2.z) + __uint_as_float(e3.z));
    f3 = (f3 + __uint_as_float(e1.w)) + (__uint_as_float(e2.w) + __uint_as_float(e3.w));
    w0 = pack2(f0, f1); w1 = pack2(f2, f3);
    if (s >= 0) sts64(mem_addr + hc * 8, w0, w1);
  }
  __syncwarp();
  const uint32_t n0 = __shfl_xor_sync(0xffffffffu, w0, 1), n1 = __shfl_xor_sync(0xffffffffu, w1, 1);
  mbar_arrive_if(bar + B_AG + (x == 2 ? 32 : 0), lane == 0);
  if (act && s >= 0) {
    const uint32_t y0 = hc ? n0 : w0, y1 = hc ? n1 : w1, y2 = hc ? w0 : n0, y3 = hc ? w1 : n1;
    st_async16(d0, y0, y1, y2, y3, e0);
    st_async16(d1, y0, y1, y2, y3, e1_);
    st_async16(d2, y0, y1, y2, y3, e2_);
    if (!hc) st_async16(d3, y0, y1, y2, y3, e3_);
  }
  __syncwarp();
  if (P) PROF(23);
}

__global__ void __launch_bounds__(NTHREADS, 1)
chain_kernel(const __grid_constant__ Maps maps, const bf16* __restrict__ mem0, const bf16* x_in, const bf16* Wq, const bf16* Wk, const bf16* Wv,
             const bf16* Wo, uint32_t zero) {
  extern __shared__ __align__(1024) unsigned char smem_raw[];
  const uint32_t sb = smem_u32(smem_raw);
  const int tid = __shfl_sync(0xffffffffu, (int)threadIdx.x, threadIdx.x & 31);
  const int warp = __shfl_sync(0xffffffffu, tid >> 5, 0), lane = tid & 31;
  const int rank = blockIdx.x & 15;
  const int cl = blockIdx.x >> 4;
  const int bid = cl * 16 + rank;
  const int gi = rank >> 1, a = rank & 1, head = cl * 8 + gi;
  const uint32_t t0 = clk32();
  const uint32_t bar = sb + SM_BAR;
  const uint32_t sl = sb + lane * 16;
  TR_T(trs);
  auto krow = [&](int sp) { const int idx = sp >> 1; const int p = idx < 8 ? ((gi + idx) & 7) : 8; return 288 * a + 32 * p + 16 * (sp & 1); };
  if (tid == 32) atomicAdd(&g_resident, 1u);
  const int ln_r8 = ((bid & 3) * 4 + warp / 3) + (bid >> 2) * 16, ln_w = warp % 3;
  uint4 lnv[6];
  {
    const uint4* src = reinterpret_cast<const uint4*>(x_in + (size_t)(ln_r8 * 8 + (lane >> 2)) * DM) + ln_w * 24 + (lane & 3);
#pragma unroll
    for (int t = 0; t < 6; t++) lnv[t] = __ldg(src + t * 4);
  }
  if (tid >= 96) {
    const int i = tid - 96, idx = i >> 5, t = lane >> 2, j = lane & 3;
    const int p = idx < 8 ? ((gi + idx) & 7) : 8;
    const uint32_t* src = reinterpret_cast<const uint32_t*>(mem0 + t * DM + 288 * a + 32 * p + 2 * j);
    sts128(sb + SM_MEM + i * 16, src[0], src[4], src[8], src[12]);
    if (i < 216) sts128(sb + SM_MB + i * 16, 0, 0, 0, 0);
  }
  PROF0(39);
  if (tid >= 64 && tid < 68) asm volatile("prefetch.tensormap [%0];" :: "l"(&maps.q + (tid - 64)) : "memory");
  if (warp == 0) {
    if (lane == 0) {
      mbar_init(bar + B_AG, 2); mbar_init(bar + B_AG + 8, 1); mbar_init(bar + B_AG + 16, 1); mbar_init(bar + B_AG + 24, 1); mbar_init(bar + B_AG + 32, 2);
      mbar_init(bar + B_XQK, 1); mbar_init(bar + B_XV, 9); mbar_init(bar + B_RS, 2); mbar_init(bar + B_KV, 1); mbar_init(bar + B_L, 1);
      for (int i = 0; i < 5; i++) mbar_init(bar + B_W + i * 8, 1);
      asm volatile("fence.mbarrier_init.release.cluster;" ::: "memory");
      mbar_expect(bar + B_W, 20 * SLOT); mbar_expect(bar + B_W + 8, 16 * SLOT); mbar_expect(bar + B_W + 16, 9 * SLOT);
      mbar_expect(bar + B_W + 24, 5 * 16384); mbar_expect(bar + B_W + 32, 9 * SLOT);
    }
    __syncwarp();
  }
  {
    const int g = lane >> 2, j = lane & 3;
    const uint32_t red = sb + SM_S + (warp / 3) * 256;
    float f[48];
#pragma unroll
    for (int t = 0; t < 6; t++) {
      f[t * 8 + 0] = bflo(lnv[t].x); f[t * 8 + 1] = bfhi(lnv[t].x); f[t * 8 + 2] = bflo(lnv[t].y); f[t * 8 + 3] = bfhi(lnv[t].y);
      f[t * 8 + 4] = bflo(lnv[t].z); f[t * 8 + 5] = bfhi(lnv[t].z); f[t * 8 + 6] = bflo(lnv[t].w); f[t * 8 + 7] = bfhi(lnv[t].w);
    }
    float sum = 0.f;
#pragma unroll
    for (int i = 0; i < 48; i++) sum += f[i];
    sum += __shfl_xor_sync(~0u, sum, 1); sum += __shfl_xor_sync(~0u, sum, 2);
    if (j == 0) sts32(red + g * 16 + ln_w * 4, __float_as_uint(sum));
    PROF0(40);
    __syncthreads();
    uint4 r = lds128(red + g * 16);
    const float mean = (__uint_as_float(r.x) + __uint_as_float(r.y) + __uint_as_float(r.z)) * (1.f / DM);
    float q = 0.f;
#pragma unroll
    for (int i = 0; i < 48; i++) { f[i] -= mean; q = fmaf(f[i], f[i], q); }
    q += __shfl_xor_sync(~0u, q, 1); q += __shfl_xor_sync(~0u, q, 2);
    if (j == 0) sts32(red + 128 + g * 16 + ln_w * 4, __float_as_uint(q));
    __syncthreads();
    r = lds128(red + 128 + g * 16);
    const float rs = rsqrtf((__uint_as_float(r.x) + __uint_as_float(r.y) + __uint_as_float(r.z)) * (1.f / DM) + 1e-5f);
    uint4* dst = g_xnT + ((size_t)(ln_r8 >> 4) * 9 + ln_w * 3) * 1024 + (ln_r8 & 15) * 64 + j * 8 + g;
#pragma unroll
    for (int t = 0; t < 6; t++)
      stg128(dst + (t >> 1) * 1024 + (t & 1) * 32, pack2(f[t * 8] * rs, f[t * 8 + 1] * rs), pack2(f[t * 8 + 2] * rs, f[t * 8 + 3] * rs),
             pack2(f[t * 8 + 4] * rs, f[t * 8 + 5] * rs), pack2(f[t * 8 + 6] * rs, f[t * 8 + 7] * rs));
  }
  PROF0(41);
  __syncthreads();
  if (tid == 352) {
    asm volatile("red.release.gpu.global.add.u32 [%0], 1;" :: "l"(&g_cntX[bid < 4 ? 0 : 32]) : "memory");
  }
  __syncwarp();
  __syncwarp();
  PROF0(42);
  cluster_sync();
  PROF0(43);
  if (warp < 3) {
    if (lane == 0) {
      if (warp != 1) {
        const int m = warp >> 1;
        const CUtensorMap* mp = m ? &maps.q : &maps.k;
        for (int u = 0; u < 10; u++) tma3d(sb + SM_WO + (2 * u + 1 - m) * SLOT, mp, krow(NX + u), head * 2, bar + B_W);
        for (int u = 0; u < 8; u++) tma3d(sb + SM_X + (2 * u + 1 - m) * SLOT, mp, krow(u), head * 2, bar + B_W + 8);
      } else {
        for (int u = 0; u < 9; u++) tma3d(sb + SM_V2 + (4 + u) * SLOT, &maps.v, krow(NV2 + u), head * 2, bar + B_W + 16);
        for (int u = 0; u < 4; u++) tma3d(sb + SM_V2 + u * SLOT, &maps.v, krow(u), head * 2, bar + B_W + 32);
      }
    }
    __syncwarp();
  }

  if (warp < 8) {
    asm volatile("setmaxnreg.inc.sync.aligned.u32 %0;" :: "n"(REG_C));
    const int w = warp;
    const uint32_t wl = sb + (w >> 2) * 2048 + frag_off(lane, w & 3);
    const uint32_t wo = sb + SM_WO + (w >> 1) * 16384 + frag_off(lane, (w & 1) * 2);
    uint32_t Pqk[18 - NX][2][4], Pv[NPV][4];
    uint32_t Xqk[NX][2][4];
#pragma unroll
    for (int u = 0; u < 20; u++) for (int q = 0; q < 4; q++) Pqk[u >> 1][u & 1][q] = 0;
#pragma unroll
    for (int u = 0; u < NPV; u++) for (int q = 0; q < 4; q++) Pv[u][q] = 0;
#pragma unroll
    for (int u = 0; u < 2 * NX; u++) for (int q = 0; q < 4; q++) Xqk[u >> 1][u & 1][q] = 0;
    const uint32_t partner = rank ^ 1;
    const uint32_t pd = __shfl_sync(~0u, mapa(sb, partner) - sb, 0), od = __shfl_sync(~0u, mapa(sb, 2 * w + a) - sb, 0);
    const bool late = STAGGER && w >= 4;
    const uint32_t ag = bar + B_AG + (late ? 8 : 0);

    for (int s = -1; s < NSEG; s++) {
      const uint32_t par = s & 1;
      float q0[4] = {0.f, 0.f, 0.f, 0.f}, k0[4] = {0.f, 0.f, 0.f, 0.f}, q1[4] = {0.f, 0.f, 0.f, 0.f}, k1[4] = {0.f, 0.f, 0.f, 0.f};
      uint4 B[9] = {};
      uint32_t V2[NV2][4];
      auto qk = [&](int idx) {
        const int s0 = 2 * idx, s1 = 2 * idx + 1;
        if (s0 < NX) { mma16816(q0, Xqk[s0][0], B[idx].x, B[idx].y); mma16816(k0, Xqk[s0][1], B[idx].x, B[idx].y); }
        else { mma16816(q0, Pqk[s0 - NX][0], B[idx].x, B[idx].y); mma16816(k0, Pqk[s0 - NX][1], B[idx].x, B[idx].y); }
        if (s1 < NX) { mma16816(q1, Xqk[s1][0], B[idx].z, B[idx].w); mma16816(k1, Xqk[s1][1], B[idx].z, B[idx].w); }
        else { mma16816(q1, Pqk[s1 - NX][0], B[idx].z, B[idx].w); mma16816(k1, Pqk[s1 - NX][1], B[idx].z, B[idx].w); }
      };
      mbar_wait(bar + B_AG, par, t0);
      if (w == 0) { PROF(0); PROFN(24); PROFS(); }
      B[0] = lds128(sl + SM_MEM);
      qk(0);
      ldsm4t(V2[0], wl + SM_V2); ldsm4t(V2[1], wl + SM_V2 + SLOT);
      if (late) mbar_wait(bar + B_AG + 8, par, t0);
      mbar_wait(ag + 8, par, t0);
      if (w == 0) PROF(1);
      B[1] = lds128(sl + SM_MEM + 512); B[2] = lds128(sl + SM_MEM + 1024);
      bool ok = mbar_try(ag + 16, par);
      qk(1);
      if (!ok) mbar_wait(ag + 16, par, t0);
      B[3] = lds128(sl + SM_MEM + 1536); B[4] = lds128(sl + SM_MEM + 2048);
      ok = mbar_try(ag + 24, par);
      qk(2);
      ldsm4t(V2[2], wl + SM_V2 + 2 * SLOT); ldsm4t(V2[3], wl + SM_V2 + 3 * SLOT);
      qk(3);
      if (!ok) mbar_wait(ag + 24, par, t0);
      if (w == 0) PROF(2);
      B[5] = lds128(sl + SM_MEM + 2560); B[6] = lds128(sl + SM_MEM + 3072);
      ok = mbar_try(bar + B_AG + 32, par);
      qk(4);
      ldsm4t(V2[4], wl + SM_V2 + 4 * SLOT); ldsm4t(V2[5], wl + SM_V2 + 5 * SLOT);
      qk(5);
      if (!ok) mbar_wait(bar + B_AG + 32, par, t0);
      if (w == 0) PROF(3);
      B[7] = lds128(sl + SM_MEM + 3584); B[8] = lds128(sl + SM_MEM + 4096);
      qk(6);
      ldsm4t(V2[6], wl + SM_V2 + 6 * SLOT); ldsm4t(V2[7], wl + SM_V2 + 7 * SLOT);
      qk(7);
      if (late) bar_arrive(BAR_AB, 256);
      qk(8);
      const uint32_t pq0 = pack2(q0[0] + q1[0], q0[1] + q1[1]);
      {
        const uint32_t c0 = movmat(pq0), c1 = movmat(pack2(q0[2] + q1[2], q0[3] + q1[3]));
        const uint32_t c2 = movmat(pack2(k0[0] + k1[0], k0[1] + k1[1])), c3 = movmat(pack2(k0[2] + k1[2], k0[3] + k1[3]));
        const bool swp = sl & 128;
        const uint32_t y0 = swp ? c2 : c0, y1 = swp ? c3 : c1, y2 = swp ? c0 : c2, y3 = swp ? c1 : c3;
        if (s >= 0) st_async16(sl + (pd + w * 512 + SM_XQK), y0, y1, y2, y3, bar + pd + B_XQK);
        sts128(sl + (w * 512 + SM_OQK), y0, y1, y2, y3);
        bar_arrive(BAR_OQK, NTHREADS);
      }
      if (w == 0) PROF(4);
      if (w == 4) PROF(14);
      ldsm4t(V2[8], wl + SM_V2 + 8 * SLOT);
      if (STAGGER && !late) bar_sync(BAR_AB, 256);
      const float vz = __uint_as_float(pq0 & zero);
      float v[4][4] = {{vz, 0.f, 0.f, 0.f}, {vz, 0.f, 0.f, 0.f}, {vz, 0.f, 0.f, 0.f}, {vz, 0.f, 0.f, 0.f}};
      uint32_t WO[16][4];
      if (s == 0) mbar_wait(bar + B_W + 24, 0, t0);
#pragma unroll
      for (int idx = 0; idx < 9; idx++) {
        const int s0 = 2 * idx, s1 = 2 * idx + 1;
        if (s0 < NV2) mma16816(v[s0 & 3], V2[s0], B[idx].x, B[idx].y); else mma16816(v[s0 & 3], Pv[s0 - NV2], B[idx].x, B[idx].y);
        if (s1 < NV2) mma16816(v[s1 & 3], V2[s1], B[idx].z, B[idx].w); else mma16816(v[s1 & 3], Pv[s1 - NV2], B[idx].z, B[idx].w);
        if (idx >= 9 - WEARLY) ldsm4t(WO[idx - (9 - WEARLY)], wo + (idx - (9 - WEARLY)) * 2048);
      }
      {
        const uint32_t vo0 = pack2((v[0][0] + v[1][0]) + (v[2][0] + v[3][0]), (v[0][1] + v[1][1]) + (v[2][1] + v[3][1]));
        const uint32_t vo1 = pack2((v[0][2] + v[1][2]) + (v[2][2] + v[3][2]), (v[0][3] + v[1][3]) + (v[2][3] + v[3][3]));
        const uint32_t l8 = (sl - sb) >> 1;
        if (s >= 0) st_async8(l8 + (sb + pd + w * 256 + SM_XV), vo0, vo1, bar + pd + B_XV);
        sts64(l8 + (sb + w * 256 + SM_OV), vo0, vo1);
        __syncwarp();
        mbar_arrive_if(bar + B_XV, sl == sb && s >= 0);
      }
      if (w == 0) PROF(5);
      if (s == NSEG - 1) break;
#pragma unroll
      for (int u = WEARLY; u < 16; u++) ldsm4t(WO[u], dep(u >= 8 ? wo ^ 32 : wo, WO[(u < 16 - WLATE ? u : 16 - WLATE) - 1][0], zero) + (u & 7) * 2048);
      if (w == 0) PROF(6);
      bar_sync(BAR_O, NTHREADS);
      {
        float m0[4] = {0.f, 0.f, 0.f, 0.f}, m1[4] = {0.f, 0.f, 0.f, 0.f}, m2[4] = {0.f, 0.f, 0.f, 0.f}, m3[4] = {0.f, 0.f, 0.f, 0.f};
        uint32_t ob[4][4];
        bool okl = false;
#pragma unroll
        for (int u = 0; u < 4; u++) ldsm4t(ob[u], sl + SM_O + u * 512);
#pragma unroll
        for (int u = 0; u < 3; u++) {
          mma16816(m0, WO[2 * u], ob[u][0], ob[u][1]);     mma16816(m1, WO[8 + 2 * u], ob[u][0], ob[u][1]);
          mma16816(m2, WO[2 * u + 1], ob[u][2], ob[u][3]); mma16816(m3, WO[8 + 2 * u + 1], ob[u][2], ob[u][3]);
          if (u == 1) okl = mbar_try(bar + B_L, par);
        }
        mma16816(m0, WO[6], ob[3][0], ob[3][1]); mma16816(m1, WO[14], ob[3][0], ob[3][1]);
        if (!okl) mbar_wait(bar + B_L, par, t0);
        const uint2 iv = lds64(sb + SM_INV + ((sl >> 1) & 24));
        mma16816(m2, WO[7], ob[3][2], ob[3][3]); mma16816(m3, WO[15], ob[3][2], ob[3][3]);
        const float i0 = __uint_as_float(iv.x), i1 = __uint_as_float(iv.y);
        const uint32_t c0 = movmat(pack2((m0[0] + m2[0]) * i0, (m0[1] + m2[1]) * i1)), c1 = movmat(pack2((m0[2] + m2[2]) * i0, (m0[3] + m2[3]) * i1));
        const uint32_t c2 = movmat(pack2((m1[0] + m3[0]) * i0, (m1[1] + m3[1]) * i1)), c3 = movmat(pack2((m1[2] + m3[2]) * i0, (m1[3] + m3[3]) * i1));
        if (w == gi) {
          sts128(sl + SM_RS + gi * 576, c0, c1, c2, c3);
          __syncwarp();
          mbar_arrive_if(bar + B_RS, sl == sb && s >= 0);
        } else if (s >= 0) {
          st_async16(sl + (od + SM_RS + gi * 576), c0, c1, c2, c3, bar + od + B_RS);
        }
      }
      if (w == 0) PROF(10);
      if (w == 4) PROF(15);
      if (s < 0) {
        if (w == 3) PROF1(44);
        mbar_wait(bar + B_W, 0, t0);
#pragma unroll
        for (int u = 0; u < 20; u++) ldsm4t(Pqk[u >> 1][u & 1], wl + SM_WO + u * SLOT);
        mbar_wait(bar + B_W + 16, 0, t0);
#pragma unroll
        for (int u = 0; u < NPV; u++) ldsm4t(Pv[u], wl + SM_V2 + (4 + u) * SLOT);
        if (w == 3) PROF1(45);
        bar_sync(BAR_C, 256);
        if (w == 0) {
          if (lane < 5) tma3d(sb + SM_V2 + (4 + lane) * SLOT, &maps.v, krow(4 + lane), head * 2, bar + B_W + 32);
          else if (lane < 10) tma2d(sb + SM_WO + (lane - 5) * 16384, &maps.o, 288 * a + 64 * (lane - 5), head * DH, bar + B_W + 24);
          __syncwarp();
        }
        bar_arrive(BAR_ALL, NTHREADS);
        mbar_wait(bar + B_W + 8, 0, t0);
        mbar_wait(bar + B_W + 32, 0, t0);
      }
      uint32_t keep = 0;
#pragma unroll
      for (int u = 0; u < 2 * NX; u++) {
        if (u == 6) mbar_wait(bar + B_RS, par, t0);
        if (u == 7 || u == 15) { float dz[4] = {0.f, 0.f, 0.f, 0.f}; mma16816(dz, Xqk[(u - 1) >> 1][(u - 1) & 1], zero, zero); keep = __float_as_uint(dz[0]); }
        ldsm4t(Xqk[u >> 1][u & 1], (u < 1 ? wl : dep(wl, (u == 7 || u == 15) && KEEPALIVE ? keep : Xqk[(u - 1) >> 1][(u - 1) & 1][0], zero)) + SM_X + u * SLOT);
      }
      if (w == 0) PROF(11);
    }
    __syncwarp();
    cluster_sync();
  } else {
    asm volatile("setmaxnreg.dec.sync.aligned.u32 %0;" :: "n"(REG_A));
    const int x = warp - 8;
    const int g = lane >> 2, j = lane & 3;
    const uint32_t sa = sb + SM_S + x * 512 + (32 * j + 4 * (g >> 1) + (g & 1)) * 4;
    const uint32_t sq = sl + (lane & 8);
    if (x < 2) {
      bar_arrive(BAR_ALL, NTHREADS);
      for (int s = -1; s < NSEG - 1; s++) {
        const uint32_t par = s & 1;
        uint4 R[8];
        if (s == 0) mbar_wait(bar + B_W + 24, 0, t0);
        mbar_wait(bar + B_KV, par, t0);
#pragma unroll
        for (int u = 0; u < 8; u++) R[u] = lds128(sl + SM_KX + x * 4096 + u * 512);
        float c0[4] = {0.f, 0.f, 0.f, 0.f}, c1[4] = {0.f, 0.f, 0.f, 0.f}, c2[4] = {0.f, 0.f, 0.f, 0.f}, c3[4] = {0.f, 0.f, 0.f, 0.f};
        bar_sync(BAR_OQK, NTHREADS);
        uint2 o[8];
#pragma unroll
        for (int u = 0; u < 8; u++) o[u] = lds64(sq + SM_OQK + u * 512);
        if (x == 0) PROF(16);
        mbar_wait(bar + B_XQK, par, t0);
        if (x == 0) PROF(17);
        {
          uint2 b[8];
#pragma unroll
          for (int u = 0; u < 8; u++) b[u] = lds64(sq + SM_XQK + u * 512);
#pragma unroll
          for (int u = 0; u < 8; u++) { b[u].x = hadd2bf(b[u].x, o[u].x); b[u].y = hadd2bf(b[u].y, o[u].y); }
          mmaq(c0, R[0], b[0].x, b[0].y); mmaq(c1, R[1], b[1].x, b[1].y); mmaq(c2, R[2], b[2].x, b[2].y); mmaq(c3, R[3], b[3].x, b[3].y);
          mmaq(c0, R[4], b[4].x, b[4].y); mmaq(c1, R[5], b[5].x, b[5].y); mmaq(c2, R[6], b[6].x, b[6].y); mmaq(c3, R[7], b[7].x, b[7].y);
        }
        sts32(sa, __float_as_uint((c0[0] + c1[0]) + (c2[0] + c3[0])));
        sts32(sa + 64, __float_as_uint((c0[1] + c1[1]) + (c2[1] + c3[1])));
        sts32(sa + 8, __float_as_uint((c0[2] + c1[2]) + (c2[2] + c3[2])));
        sts32(sa + 72, __float_as_uint((c0[3] + c1[3]) + (c2[3] + c3[3])));
        if (x == 0) PROF(18);
        uint32_t WX[8][4];
        uint4 vmo;
        softmax_pv<true>(s, x, sb, sl, bar, lane, a, head, t0, WX, vmo, x == 0);
        {
          float m0[4] = {0.f, 0.f, 0.f, 0.f}, m1[4] = {0.f, 0.f, 0.f, 0.f}, m2[4] = {0.f, 0.f, 0.f, 0.f}, m3[4] = {0.f, 0.f, 0.f, 0.f};
          uint32_t ob[4][4];
#pragma unroll
          for (int u = 0; u < 4; u++) ldsm4t(ob[u], sl + SM_O + u * 512);
          const int ln = opaque(lane);
          const uint32_t r_rs2 = mapa(sb + SM_RS + gi * 576 + (32 + (ln & 3)) * 16 + x * 8, 2 * (ln >> 2) + a), r_rsb2 = mapa(bar + B_RS, 2 * (ln >> 2) + a);
          mma16816(m0, WX[0], ob[0][0], ob[0][1]); mma16816(m1, WX[1], ob[0][2], ob[0][3]);
          mma16816(m2, WX[2], ob[1][0], ob[1][1]); mma16816(m3, WX[3], ob[1][2], ob[1][3]);
          mma16816(m0, WX[4], ob[2][0], ob[2][1]); mma16816(m1, WX[5], ob[2][2], ob[2][3]);
          mma16816(m2, WX[6], ob[3][0], ob[3][1]); mma16816(m3, WX[7], ob[3][2], ob[3][3]);
          mbar_wait(bar + B_L, par, t0);
          const uint2 iv = lds64(sb + SM_INV + (ln & 3) * 8);
          const float i0 = __uint_as_float(iv.x), i1 = __uint_as_float(iv.y);
          const uint32_t d0 = movmat(pack2(((m0[0] + m1[0]) + (m2[0] + m3[0])) * i0, ((m0[1] + m1[1]) + (m2[1] + m3[1])) * i1));
          const uint32_t d1 = movmat(pack2(((m0[2] + m1[2]) + (m2[2] + m3[2])) * i0, ((m0[3] + m1[3]) + (m2[3] + m3[3])) * i1));
          if (s >= 0) st_async8(r_rs2, d0, d1, r_rsb2);
          if (a == 0 && s >= 0) g_Vmf[((size_t)head * NSEG + s) * 128 + x * 32 + ln] = vmo;
        }
        if (x == 0) PROF(19);
        reduce_exchange(x, gi, a, s, sb, bar, lane, t0, x == 0, bid);
      }
      bar_sync(BAR_OQK, NTHREADS);
    } else {
      const unsigned epoch = g_epoch + 1;
      const uint4* kx_g = g_Kf + (size_t)head * 128 * 256;
      const uint4* vx_g = g_Vf + (size_t)head * NSEG * 512;
      const int hh = x - 2;
      const uint32_t sm_ = sa - hh * 512 + hh * 8;
      uint4* const km_ptr = g_Kmf + (size_t)head * NSEG * 128 + hh * 64 + lane;
      if (x == 2) bar_arrive(BAR_ALL, NTHREADS);
      for (int s = -1; s < NSEG; s++) {
        const uint32_t par = s & 1;
        uint2 Q[4], K[4], oq[4], okk[4];
        if (s < NSEG - 1) mbar_wait(bar + B_KV, par, t0);
        bar_sync(BAR_OQK, NTHREADS);
#pragma unroll
        for (int u = 0; u < 4; u++) { Q[u] = lds64(sq + SM_OQK + (hh * 4 + u) * 512); K[u] = lds64((sq ^ 8) + SM_OQK + (hh * 4 + u) * 512); }
        mbar_wait(bar + B_XQK, par, t0);
        float c0[4] = {0.f, 0.f, 0.f, 0.f}, c1[4] = {0.f, 0.f, 0.f, 0.f}, c2[4] = {0.f, 0.f, 0.f, 0.f}, c3[4] = {0.f, 0.f, 0.f, 0.f};
#pragma unroll
        for (int u = 0; u < 4; u++) { oq[u] = lds64(sq + SM_XQK + (hh * 4 + u) * 512); okk[u] = lds64((sq ^ 8) + SM_XQK + (hh * 4 + u) * 512); }
#pragma unroll
        for (int u = 0; u < 4; u++) {
          Q[u].x = hadd2bf(Q[u].x, oq[u].x); Q[u].y = hadd2bf(Q[u].y, oq[u].y); K[u].x = hadd2bf(K[u].x, okk[u].x); K[u].y = hadd2bf(K[u].y, okk[u].y);
        }
#pragma unroll
        for (int u = 0; u < 4; u += 2) {
          mma1688(c0, K[u].x, K[u].y, Q[u].x);
          mma1688(c1, K[u].x, K[u].y, Q[u].y);
          mma1688(c2, K[u + 1].x, K[u + 1].y, Q[u + 1].x);
          mma1688(c3, K[u + 1].x, K[u + 1].y, Q[u + 1].y);
        }
        sts32(sm_, __float_as_uint((c0[0] + c1[2]) + (c2[0] + c3[2])));
        sts32(sm_ + 64, __float_as_uint((c0[1] + c1[3]) + (c2[1] + c3[3])));
        uint32_t dummy[8][4]; uint4 dummy4;
        if (s < NSEG - 1) softmax_pv<false>(s, x, sb, sl, bar, lane, a, head, t0, dummy, dummy4, 0);
        if (a == 0 && s >= 0) {
          km_ptr[(size_t)s * 128] = make_uint4(K[0].x, K[0].y, K[1].x, K[1].y);
          km_ptr[(size_t)s * 128 + 32] = make_uint4(K[2].x, K[2].y, K[3].x, K[3].y);
        }
        if (s == NSEG - 1) break;
        if (x == 2) {
          reduce_exchange(x, gi, a, s, sb, bar, lane, t0, 0, bid);
          if (lane == 0) mbar_expect(bar + B_RS, RS_BYTES);
        } else {
          if (lane == 0 && s >= 0 && s + 1 < NSEG - 1) {
            mbar_expect(bar + B_KV, 16384);
            bulk_g2s(sb + SM_KX, kx_g + (size_t)(s + 1) * 512, 8192, bar + B_KV);
            bulk_g2s(sb + SM_VX, vx_g + (size_t)(s + 1) * 512, 8192, bar + B_KV);
          }
          __syncwarp();
          mbar_wait(bar + B_RS, par, t0);
          if (lane == 0) {
            const int nb = s < 0 ? 0 : 1024;
            mbar_expect(bar + B_AG + 8, nb); mbar_expect(bar + B_AG + 16, nb); mbar_expect(bar + B_AG + 24, nb); mbar_expect(bar + B_AG + 32, s < 0 ? 0 : 960);
            mbar_expect(bar + B_XQK, 4096); mbar_expect(bar + B_XV, 2048);
            if (a == 0 && (s & 3) == 0 && s > 0) { st_release(&g_memflag[head * 8], epoch * 64 + s); if (bid == 0) TR_LOG(9 | (((s - 1) >> 2) << 24), trs, trs); }
            if ((s & 3) == 2 && s + 2 < NSEG) {
              while (ld_acquire(&g_kvflag[((s + 2) >> 2) * 64 + head]) != epoch) { if (timed_out(t0)) break; }
              while (ld_acquire(&g_kvflag[((s + 2) >> 2) * 64 + 32 + head]) != epoch) { if (timed_out(t0)) break; }
              asm volatile("fence.proxy.async.global;" ::: "memory");
              asm volatile("cp.async.bulk.prefetch.L2.global [%0], 32768;" :: "l"(kx_g + (size_t)(s + 2) * 512) : "memory");
              asm volatile("cp.async.bulk.prefetch.L2.global [%0], 32768;" :: "l"(vx_g + (size_t)(s + 2) * 512) : "memory");
            }
          }
          __syncwarp();
          if (s >= 0) {
            float dz[4] = {0.f, 0.f, 0.f, 0.f};
            while (true) {
              mma16816(dz, zero, zero, zero, zero, zero, zero);
              if (__all_sync(~0u, mbar_test(bar + B_AG + __float_as_uint(dz[0]), par ^ 1) || timed_out(t0))) break;
              __nanosleep(KEEPALIVE);
            }
          }
          if (s < 0) {
            __syncwarp();
            bar_sync(BAR_ALL, NTHREADS);
            if (lane == 0) {
              while (ld_acquire(&g_kvflag[head]) != epoch) { if (timed_out(t0)) break; __nanosleep(100); }
              while (ld_acquire(&g_kvflag[32 + head]) != epoch) { if (timed_out(t0)) break; __nanosleep(100); }
              asm volatile("fence.proxy.async.global;" ::: "memory");
              mbar_expect(bar + B_KV, 16384);
              bulk_g2s(sb + SM_KX, kx_g, 8192, bar + B_KV);
              bulk_g2s(sb + SM_VX, vx_g, 8192, bar + B_KV);
            }
          }
        }
        __syncwarp();
      }
    }
    {
      mbar_wait(bar + B_XV, (NSEG - 1) & 1, t0);
      const uint32_t lv = sb + x * 512 + lane * 8;
      const uint2 ov0 = lds64(lv + SM_OV), xv0 = lds64(lv + SM_XV), ov1 = lds64(lv + SM_OV + 256), xv1 = lds64(lv + SM_XV + 256);
      if (a == 0) g_Vmf[((size_t)head * NSEG + NSEG - 1) * 128 + x * 32 + lane] = make_uint4(hadd2bf(ov0.x, xv0.x), hadd2bf(ov0.y, xv0.y), hadd2bf(ov1.x, xv1.x), hadd2bf(ov1.y, xv1.y));
      bar_sync(BAR_S, 128);
      if (x == 3 && a == 0 && lane == 0) { st_release(&g_memflag[head * 8], (g_epoch + 1) * 64 + 64); if (bid == 0) TR_LOG(9 | (15 << 24), trs, trs); }
    }
    __syncwarp();
    cluster_sync();
  }
}
}
__device__ __align__(1024) uint4 g_hnT[NRB * 9 * 1024];
__device__ __align__(1024) uint4 g_oT[NRB * 64 * 1024];
__device__ __align__(1024) uint4 g_gT[NRB * 72 * 1024];
constexpr int MAXSPLIT = 6;
__device__ __align__(1024) uint4 g_p1[MAXSPLIT * 256 * 18 * 32];
__device__ __align__(1024) uint4 g_p2[MAXSPLIT * 256 * 18 * 32];
__device__ __align__(1024) uint4 g_hT[256 * 18 * 32];

__global__ void gate_kernel() {
  const uint32_t t0 = clk32();
  const unsigned need = (g_epoch + 1) * 64u;
  while ((int)(ld_relaxed(&g_resident) - need) < 0) { if (timed_out(t0)) break; }
}
namespace mega {
constexpr int NS = 5;
constexpr int SM_B = 0, SM_A = 9 * 16384, SM_BAR = SM_A + NS * 16384;
constexpr int B_FA = 0, B_EA = NS * 8, B_FB = 2 * NS * 8, B_EB = B_FB + 96, B_D = B_EB + 24, B_TK = B_D + 32, B_QF = B_TK + 32, B_QE = B_QF + 16,
              B_PD = B_QE + 16, B_PE = B_PD + 16, B_BF = B_PE + 16, B_BE = B_BF + 8;
constexpr int SM_DESC = SM_BAR + 512;
constexpr int SM_TQ = SM_DESC + 64;
constexpr int SM_TK = SM_TQ + 32;
constexpr int SM_PUB = SM_TK + 16;
constexpr int SM_RED = SM_PUB + 16;
constexpr int SM_TOTAL = SM_RED + 256;
enum { T_K = 0, T_V = 1, T_QA = 2, T_OP = 3, T_F1 = 4, T_F2 = 5, T_END = 6 };
constexpr int NORDER = 538;
__constant__ unsigned short c_order[NORDER] = {
  1280,3328,5376,7424,9472,11520,13568,15616,17664,19712,21760,23808,25856,27904,29952,32000,34048,36096,38144,40192,
  42240,44288,46336,48384,50432,52480,54528,56576,58624,60672,62720,64768,386,2434,4482,6530,8578,10626,12674,14722,
  16770,18818,20866,22914,24962,27010,29058,31106,387,2435,4483,6531,8579,10627,12675,14723,16771,848,2896,4944,
  6992,9040,11088,13136,15184,17232,19280,21328,23376,25424,27472,29520,31568,18819,20867,22915,24963,27011,29059,31107,
  33155,35203,410,2458,4506,6554,8602,10650,12698,14746,33616,35664,37712,39760,41808,43856,45904,47952,50000,52048,
  54096,56144,58192,60240,62288,64336,16794,18842,20890,22938,24986,27034,29082,31130,434,2482,4530,6578,8626,10674,
  12722,14770,411,2459,4507,6555,8603,10651,12699,14747,16795,16818,18866,20914,22962,25010,27058,29106,31154,18843,
  20891,22939,24987,27035,29083,31131,33179,35227,388,2436,4484,6532,8580,10628,12676,14724,16772,18820,20868,22916,
  24964,27012,29060,31108,33156,35204,435,2483,4531,6579,8627,10675,12723,14771,16819,18867,20915,22963,25011,27059,
  29107,31155,33203,35251,412,2460,4508,6556,8604,10652,12700,14748,16796,18844,20892,22940,24988,27036,29084,31132,
  33180,35228,389,2437,4485,6533,8581,10629,12677,14725,16773,18821,20869,22917,24965,27013,29061,31109,33157,35205,
  413,2461,4509,6557,8605,10653,12701,14749,16797,458,2506,4554,6602,8650,10698,12746,14794,16842,18890,20938,
  22986,25034,27082,29130,31178,18845,20893,22941,24989,27037,29085,31133,33181,35229,436,2484,4532,6580,8628,10676,
  12724,14772,16820,18868,20916,22964,25012,27060,29108,31156,33204,35252,459,2507,4555,6603,8651,10699,12747,14795,
  16843,18891,20939,22987,25035,27083,29131,31179,33227,35275,354,2402,4450,6498,8546,10594,12642,14690,437,2485,
  4533,6581,8629,10677,12725,14773,16821,18869,20917,22965,25013,27061,29109,31157,33205,35253,16738,18786,20834,22882,
  24930,26978,29026,31074,355,2403,4451,6499,8547,10595,12643,14691,16739,370,2418,4466,6514,8562,10610,12658,
  14706,18787,20835,22883,24931,26979,29027,31075,33123,35171,16754,18802,20850,22898,24946,26994,29042,31090,460,2508,
  4556,6604,8652,10700,12748,14796,16844,18892,20940,22988,25036,27084,29132,31180,33228,35276,356,2404,4452,6500,
  8548,10596,12644,14692,16740,461,2509,4557,6605,8653,10701,12749,14797,16845,18893,20941,22989,25037,27085,29133,
  31181,33229,35277,243,2291,4339,6387,8435,10483,12531,14579,16627,18675,20723,22771,24819,26867,28915,30963,33011,
  35059,251,2299,4347,6395,8443,10491,12539,14587,16635,18683,20731,22779,24827,26875,28923,30971,33019,35067,18788,
  20836,22884,24932,26980,29028,31076,33124,35172,357,2405,4453,6501,8549,10597,12645,14693,16741,244,2292,4340,
  6388,8436,10484,12532,14580,16628,18789,20837,22885,24933,26981,29029,31077,33125,35173,18676,20724,22772,24820,26868,
  28916,30964,33012,35060,252,2300,4348,6396,8444,10492,12540,14588,16636,18684,20732,22780,24828,26876,28924,30972,
  33020,35068,245,2293,4341,6389,8437,10485,12533,14581,16629,18677,20725,22773,24821,26869,28917,30965,33013,35061,
  253,2301,4349,6397,8445,10493,12541,14589,16637,18685,20733,22781,24829,26877,28925,30973,33021,35069,
};
constexpr int NTASK = NORDER;
constexpr int NWTASK = 2048;
constexpr int SPL = 6;
#define LATECLAIM 260
#define LATETH 1
#define PRE 2
constexpr int REG_C = 192, REG_P = 120;
static_assert(2 * REG_C + REG_P <= 504, "register pool");

__device__ unsigned g_ticket, g_wticket;
constexpr int PAD = 32;
__device__ unsigned g_cntO[NRB * 8 * PAD], g_cntP1[NRB * PAD], g_cntH[NRB * PAD], g_cntG[NRB * 8 * PAD], g_cntP2[NRB * PAD], g_done;

template <int B> struct IntC { static constexpr int value = B; };
__device__ __forceinline__ void red_release(unsigned* p) { asm volatile("red.release.gpu.global.add.u32 [%0], 1;" :: "l"(p) : "memory"); }
__device__ __forceinline__ void wait_cnt(const unsigned* p, unsigned need, int far, uint32_t t0) {
  while (true) {
    const int d = (int)(ld_relaxed(p) - need);
    if (d >= 0) break;
    if (timed_out(t0)) break;
    __nanosleep(d <= -far ? 1000 : 40);
  }
  (void)ld_acquire(p);
}
__device__ __forceinline__ float gelu_tanh(float z) {
  const float u = z * fmaf(z * z, 0.044715f * 0.7978845608028654f, 0.7978845608028654f);
  float t; asm("tanh.approx.f32 %0, %1;" : "=f"(t) : "f"(u));
  const float hz = 0.5f * z;
  return fmaf(hz, t, hz);
}
__device__ __forceinline__ void acc8(float (&f)[8], const uint4& v) {
  f[0] += bflo(v.x); f[1] += bfhi(v.x); f[2] += bflo(v.y); f[3] += bfhi(v.y);
  f[4] += bflo(v.z); f[5] += bfhi(v.z); f[6] += bflo(v.w); f[7] += bfhi(v.w);
}

__device__ __forceinline__ void arrive2_if(uint32_t local, uint32_t pd, int p, int cnt) {
  asm volatile("{ .reg .pred q; setp.ne.b32 q, %2, 0; @q mbarrier.arrive.shared::cta.b64 _, [%0], %3; @q mbarrier.arrive.shared::cluster.b64 _, [%1], %3; }"
    :: "r"(local), "r"(local + pd), "r"(p), "r"(cnt) : "memory");
}
__device__ __forceinline__ void bulk_mc(uint32_t dst, const void* src, uint32_t bytes, uint32_t bar) {
  asm volatile("cp.async.bulk.shared::cluster.global.mbarrier::complete_tx::bytes.multicast::cluster [%0], [%1], %2, [%3], %4;"
    :: "r"(dst), "l"(src), "r"(bytes), "r"(bar), "h"((uint16_t)3) : "memory");
}
__device__ __forceinline__ int op_kb0(int kc) { return kc < 2 ? 12 * kc : 4 + 10 * kc; }
__device__ __forceinline__ int task_nkb(int type, int kc) { return type == T_OP ? (kc < 2 ? 12 : 10) : type == T_F2 ? 12 : 9; }

__device__ __forceinline__ void finish(unsigned epoch) {
  if (atomicAdd(&g_done, 1u) == epoch * 3 * gridDim.x - 1) { g_ticket = 0; g_wticket = 0; g_epoch = epoch; }
}
struct Maps { CUtensorMap m[6]; };

__global__ void __launch_bounds__(384, 1)
mega_kernel(const __grid_constant__ Maps maps, const bf16* __restrict__ x, const bf16* __restrict__ b1, const bf16* __restrict__ b2,
            bf16* __restrict__ out) {
  extern __shared__ __align__(1024) unsigned char smem_raw[];
  const uint32_t sb = smem_u32(smem_raw);
  const int tid = threadIdx.x, wg = __shfl_sync(~0u, tid >> 7, 0), lane = tid & 31, w = __shfl_sync(~0u, (tid >> 5) & 3, 0);
  const uint32_t bar = sb + SM_BAR;
  const uint32_t t0 = clk32();
  if (tid == 0) {
    for (int i = 0; i < NS; i++) { mbar_init(bar + B_FA + i * 8, 1); mbar_init(bar + B_EA + i * 8, 8); }
    for (int i = 0; i < 3; i++) mbar_init(bar + B_FB + i * 8, 1);
    for (int i = 0; i < 3; i++) mbar_init(bar + B_EB + i * 8, 4);
    for (int i = 0; i < 4; i++) mbar_init(bar + B_D + i * 8, 1);
    for (int i = 0; i < 4; i++) mbar_init(bar + B_TK + i * 8, 1);
    for (int i = 0; i < 2; i++) { mbar_init(bar + B_QF + i * 8, 1); mbar_init(bar + B_QE + i * 8, 1); mbar_init(bar + B_PD + i * 8, 4); mbar_init(bar + B_PE + i * 8, 1); }
    mbar_init(bar + B_BF, 1); mbar_init(bar + B_BE, 1);
    asm volatile("fence.mbarrier_init.release.cluster;" ::: "memory");
  }
  const int rank = blockIdx.x & 1;
  const uint32_t pd = __shfl_sync(~0u, mapa(sb, rank ^ 1) - sb, 0);
  const unsigned ep0 = *(volatile unsigned*)&g_epoch;
  const unsigned epoch = ep0 + 1;
  __syncthreads();
  asm volatile("barrier.cluster.arrive.relaxed.aligned; barrier.cluster.wait.aligned;" ::: "memory");
  if (wg == 2) {
    asm volatile("setmaxnreg.dec.sync.aligned.u32 %0;" :: "n"(REG_P));
    if (w == 0) {
      {
        int st = 0, ph = 1, seq = 0, qi = 0;
        uint32_t bjob = 0, ebph = 1; int th = 3, bj = 0;
        auto bservice = [&]() {
          if (th == 3) {
            if (!mbar_test(bar + B_BF, bj & 1)) return;
            asm volatile("ld.shared.b32 %0, [%1];" : "=r"(bjob) : "r"(sb + SM_RED) : "memory");
            bjob = __shfl_sync(~0u, bjob, 0);
            th = 0; bj++;
          }
          if (!mbar_test(bar + B_EB + th * 8, ebph)) return;
          const int type = bjob & 255, sl = (bjob >> 8) & 255, kc = (bjob >> 16) & 255;
          const CUtensorMap* mp = &maps.m[type];
          const uint32_t fb = bar + B_FB + th * 8, dst = sb + SM_B + th * 49152;
          if (elect()) {
            mbar_expect(fb, 49152);
            if (type <= T_QA) tma3d(dst, mp, th * 192, sl * 2, fb);
            else if (type == T_F1) { tma5d(dst, mp, sl * 128, th * 6, fb); tma5d(dst + 24576, mp, sl * 128 + 64, th * 6, fb); }
            else {
              const int u0 = (type == T_OP ? op_kb0(kc) : kc * 12) * 2 + th * 8;
              tma5d(dst, mp, sl * 96, u0, fb); tma5d(dst + 16384, mp, sl * 96 + 32, u0, fb); tma5d(dst + 32768, mp, sl * 96 + 64, u0, fb);
            }
            if (th == 2) mbar_arrive(bar + B_BE);
          }
          if (++th == 3) ebph ^= 1;
        };
        auto pwait = [&](uint32_t b, uint32_t par) {
          while (!mbar_test(b, par)) { bservice(); if (timed_out(t0)) break; }
        };
        auto pop = [&]() {
          pwait(bar + B_QF + (qi & 1) * 8, (qi >> 1) & 1);
          uint2 e = lds64(sb + SM_TQ + (qi & 1) * 16);
          e.x = __shfl_sync(~0u, e.x, 0); e.y = __shfl_sync(~0u, e.y, 0);
          if (elect()) mbar_arrive(bar + B_QE + (qi & 1) * 8);
          qi++;
          return e;
        };
        while (true) {
          const uint2 e = pop();
          const int type = e.x & 255;
          if (type == T_END) break;
          const int sl = (e.x >> 8) & 255, kc = (e.x >> 16) & 255, rb = e.x >> 24;
          if (elect()) {
            sts64(sb + SM_DESC + (seq & 3) * 16, e.x, e.y | st | (ph << 8));
            mbar_arrive(bar + B_D + (seq & 3) * 8);
          }
          seq++;
          const int nkb = task_nkb(type, kc), kb0 = type == T_OP ? op_kb0(kc) : kc * 12;
          const uint4* A = type <= T_QA ? g_xnT : type == T_OP ? g_oT : type == T_F1 ? g_hnT : g_gT;
          const int ktot = type == T_OP ? 64 : type == T_F2 ? 72 : 9;
          const uint4* src = A + ((size_t)rb * ktot + kb0) * 1024 + rank * 512;
          bservice();
          for (int kb = 0; kb < nkb; kb++) {
            pwait(bar + B_EA + st * 8, ph);
            if (elect()) {
              mbar_expect(bar + B_FA + st * 8, 16384);
              bulk_mc(sb + SM_A + st * 16384 + rank * 8192, src, 8192, bar + B_FA + st * 8);
            }
            src += 1024;
            if (++st == NS) { st = 0; ph ^= 1; }
          }
          if (type == T_QA) {
            const size_t so = (size_t)sl * NSEG + rb * 4;
            const int mpos = (e.y >> 19) & 1 ? 2 : 4;
            for (int q = 0; q < 5; q++) {
              if (q == 4 && mpos == 4) pop();
              pwait(bar + B_EA + st * 8, ph);
              const uint32_t fa = bar + B_FA + st * 8, dst = sb + SM_A + st * 16384;
              const uint4* p = q < 2 ? g_Kf + so * 512 + q * 1024 : g_Vf + so * 512 + (q - (mpos == 2 ? 3 : 2)) * 1024;
              if (elect()) {
                mbar_expect(fa, 16384);
                if (q != mpos) bulk_g2s(dst, p, 16384, fa);
                else { bulk_g2s(dst, g_Kmf + so * 128, 8192, fa); bulk_g2s(dst + 8192, g_Vmf + so * 128, 8192, fa); }
              }
              if (++st == NS) { st = 0; ph ^= 1; }
            }
          }
        }
        while (th < 3) { bservice(); if (timed_out(t0)) break; }
        if (elect()) {
          for (int i = 0; i < 2; i++) {
            sts64(sb + SM_DESC + ((seq + i) & 3) * 16, T_END, i);
            mbar_arrive(bar + B_D + ((seq + i) & 3) * 8);
          }
        }
      }
      __syncwarp();
      asm volatile("barrier.cluster.arrive.relaxed.aligned; barrier.cluster.wait.aligned;" ::: "memory");
    } else if (w == 1) {
      if (lane == 0) {
        uint32_t fbph = 0;
        int qi = 0, tk = 0, tiles = 0, pubs = 0, pub0 = 0, pub1 = 0;
        auto service = [&]() {
          bool any = false;
          if (mbar_test(bar + B_PD, pub0 & 1)) {
            const uint2 p = lds64(sb + SM_PUB);
            mbar_arrive(bar + B_PE);
            red_release(reinterpret_cast<unsigned*>(((unsigned long long)p.y << 32) | p.x));
            pub0++; pubs++; any = true;
          }
          if (mbar_test(bar + B_PD + 8, pub1 & 1)) {
            const uint2 p = lds64(sb + SM_PUB + 8);
            mbar_arrive(bar + B_PE + 8);
            red_release(reinterpret_cast<unsigned*>(((unsigned long long)p.y << 32) | p.x));
            pub1++; pubs++; any = true;
          }
          return any;
        };
        auto can_post = [&]() { return qi == 0 || mbar_test(bar + B_QE + ((qi - 1) & 1) * 8, ((qi - 1) >> 1) & 1); };
        auto post = [&](uint32_t x, uint32_t y) {
          sts64(sb + SM_TQ + (qi & 1) * 16, x, y);
          mbar_arrive(bar + B_QF + (qi & 1) * 8);
          qi++;
        };
        while (true) {
          unsigned task;
          if (rank == 0) {
            task = atomicAdd(&g_ticket, 1u);
            asm volatile("st.async.shared::cluster.mbarrier::complete_tx::bytes.b32 [%0], %1, [%2];"
              :: "r"(sb + SM_TK + (tk & 3) * 4 + pd), "r"(task), "r"(bar + B_TK + (tk & 3) * 8 + pd) : "memory");
          } else {
            mbar_expect(bar + B_TK + (tk & 3) * 8, 4);
            while (!mbar_test(bar + B_TK + (tk & 3) * 8, (tk >> 2) & 1)) { service(); if (timed_out(t0)) break; }
            asm volatile("ld.shared.b32 %0, [%1];" : "=r"(task) : "r"(sb + SM_TK + (tk & 3) * 4) : "memory");
          }
          tk++;
          if (task >= (unsigned)NTASK) break;
          int type, sl, kc = 0, rb0, n;
          {
            const int e = c_order[task], r = e >> 11;
            type = e & 7; rb0 = (e >> 3) & 15; n = (e >> 7) & 15;
            if (type == 0) { type = rank; sl = r; }
            else {
              if (type & 1) { kc = r / 3; sl = r % 3; } else sl = r;
              sl = 2 * sl + rank;
            }
          }
          const int nkb = task_nkb(type, kc);
          auto deps_ready = [&](int rb, bool mem) -> bool {
            if (mem) return (int)(ld_acquire(&g_memflag[sl * 8]) - (epoch * 64 + rb * 4 + 4)) >= 0;
            if (type == T_QA) return ld_acquire(&g_kvflag[rb * 64 + sl]) == epoch && ld_acquire(&g_kvflag[rb * 64 + 32 + sl]) == epoch;
            if (type == T_OP) return (int)(ld_acquire(&g_cntO[(rb * 8 + kc) * PAD]) - epoch * (nkb >> 1)) >= 0;
            if (type == T_F1) return (int)(ld_acquire(&g_cntH[rb * PAD]) - epoch * 64) >= 0;
            if (type == T_F2) return (int)(ld_acquire(&g_cntG[(rb * 8 + kc) * PAD]) - epoch * 6) >= 0;
            return rb >= rb0 + 2 || (rb == 0 ? (int)(ld_acquire(&g_cntX[0]) - epoch * 4) >= 0 : (int)(ld_acquire(&g_cntX[32]) - epoch * 60) >= 0);
          };
          int t = 0;
          bool bpost = false;
          bool mem = false, rdy = false, mnow = false;
          while (t < n) {
            bool prog = false;
            if (!bpost && (tk == 1 || mbar_test(bar + B_BE, tk & 1))) {
              sts32(sb + SM_RED, type | (sl << 8) | (kc << 16));
              mbar_arrive(bar + B_BF);
              bpost = true; prog = true;
            }
            prog |= service();
            {
              const int rb = rb0 + t;
              if (!rdy && deps_ready(rb, mem)) {
                rdy = true;
                mnow = type == T_QA && !mem && deps_ready(rb, true);
                if (type > T_V || t < 2) asm volatile("fence.proxy.async.global;" ::: "memory");
              }
              if (rdy && bpost && can_post()) {
                post(type | (sl << 8) | (kc << 16) | (rb << 24), ((t == n - 1) << 16) | ((t < 2) << 17) | (fbph << 18) | (mnow << 19));
                rdy = false; prog = true;
                if (!mem) tiles++;
                if (type == T_QA && !mem && !mnow) mem = true; else { mem = false; t++; }
              }
            }
            if (!prog) { if (timed_out(t0)) break; __nanosleep(rdy ? 20 : 80); }
          }
          fbph ^= 1;
        }
        while (!can_post()) { service(); if (timed_out(t0)) break; }
        post(T_END, 0);
        while (pubs < tiles) { if (!service()) { if (timed_out(t0)) break; __nanosleep(20); } }
        finish(epoch);
      }
      __syncwarp();
      asm volatile("barrier.cluster.arrive.relaxed.aligned; barrier.cluster.wait.aligned;" ::: "memory");
    } else {
      const int uq = lane >> 3, j = lane & 3;
      int id = 0;
      if (lane == 0) id = (int)atomicAdd(&g_wticket, 1u);
      id = __shfl_sync(~0u, id, 0);
      int nl = id < 128 ? (id & 1) : NRB, nf = id < 128 ? ((id & 1) ^ 1) : NRB;
      while (nl < NRB || nf < NRB) {
        int fin = 0;
        if (lane == 0) {
          while (true) {
            const int dl = nl < NRB ? (int)(ld_relaxed(&g_cntP1[nl * PAD]) - epoch * 36) : -1000;
            const int df = nf < NRB ? (int)(ld_relaxed(&g_cntP2[nf * PAD]) - epoch * 36) : -1000;
            if (dl >= -PRE) break;
            if (df >= -PRE) { fin = 1; break; }
            if (timed_out(t0)) { fin = nl >= NRB; break; }
            __nanosleep(dl <= -36 && df <= -36 ? 500 : 100);
          }
        }
        fin = __shfl_sync(~0u, fin, 0);
        const int rb = fin ? nf : nl;
        if (fin) nf += 2; else nl += 2;
        const int r2 = rb * 64 + (id >> 1), r8 = r2 >> 2;
        const int cl = (r2 & 3) * 8 + (lane & 7), g = cl >> 2;
        uint4* hp = g_hT + ((size_t)r8 * 18 + uq) * 32 + cl;
        const uint4* p = (fin ? g_p2 : g_p1) + ((size_t)r8 * 18 + uq) * (SPL * 32) + cl;
        const size_t roff = (size_t)(r8 * 8 + g) * (DM / 2) + uq * 16 + j;
        const uint32_t* e = fin ? reinterpret_cast<const uint32_t*>(b2) + uq * 16 + j : reinterpret_cast<const uint32_t*>(x) + roff;
        const bool v4 = uq < 2;
        uint4 hv[5];
#pragma unroll
        for (int t = 0; t < 5; t++) {
          hv[t] = make_uint4(0, 0, 0, 0);
          if (t < 4 || v4) hv[t] = make_uint4(ldg32(e + t * 64), ldg32(e + t * 64 + 4), ldg32(e + t * 64 + 8), ldg32(e + t * 64 + 12));
        }
        if (lane == 0) wait_cnt(fin ? &g_cntP2[rb * PAD] : &g_cntP1[rb * PAD], epoch * 36, 36, t0);
        __syncwarp();
        TR_T(tr0);
        float s = 0.f;
#pragma unroll
        for (int b = 0; b < 2; b++) {
          uint4 v[3][SPL], r[3];
#pragma unroll
          for (int t = 0; t < 3 - b; t++) {
            const int tt = b * 3 + t;
#pragma unroll
            for (int q = 0; q < SPL; q++) { v[t][q] = make_uint4(0, 0, 0, 0); if (tt < 4 || v4) v[t][q] = ldg_cg(p + (tt * 4 * SPL + q) * 32); }
          }
          if (fin) {
#pragma unroll
            for (int t = 0; t < 3 - b; t++) { const int tt = b * 3 + t; r[t] = make_uint4(0, 0, 0, 0); if (tt < 4 || v4) r[t] = ldg_cg(hp + tt * 128); }
          }
#pragma unroll
          for (int t = 0; t < 3 - b; t++) {
            const int tt = b * 3 + t;
            float f[8] = {0.f, 0.f, 0.f, 0.f, 0.f, 0.f, 0.f, 0.f};
#pragma unroll
            for (int q = 0; q < SPL; q++) acc8(f, v[t][q]);
            acc8(f, hv[tt]);
            if (fin) acc8(f, r[t]);
            const uint4 h = make_uint4(pack2(f[0], f[1]), pack2(f[2], f[3]), pack2(f[4], f[5]), pack2(f[6], f[7]));
            hv[tt] = h;
            if (tt < 4 || v4) {
              if (fin) { uint32_t* o = reinterpret_cast<uint32_t*>(out) + roff + tt * 64; o[0] = h.x; o[4] = h.y; o[8] = h.z; o[12] = h.w; }
              else stg128(hp + tt * 128, h.x, h.y, h.z, h.w);
            }
            s += ((bflo(h.x) + bfhi(h.x)) + (bflo(h.y) + bfhi(h.y))) + ((bflo(h.z) + bfhi(h.z)) + (bflo(h.w) + bfhi(h.w)));
          }
        }
        if (!fin) {
          s += __shfl_xor_sync(~0u, s, 1); s += __shfl_xor_sync(~0u, s, 2); s += __shfl_xor_sync(~0u, s, 8); s += __shfl_xor_sync(~0u, s, 16);
          const float mean = s * (1.f / DM);
          float dv[5][8];
          float q = 0.f;
#pragma unroll
          for (int t = 0; t < 5; t++) {
            dv[t][0] = bflo(hv[t].x) - mean; dv[t][1] = bfhi(hv[t].x) - mean; dv[t][2] = bflo(hv[t].y) - mean; dv[t][3] = bfhi(hv[t].y) - mean;
            dv[t][4] = bflo(hv[t].z) - mean; dv[t][5] = bfhi(hv[t].z) - mean; dv[t][6] = bflo(hv[t].w) - mean; dv[t][7] = bfhi(hv[t].w) - mean;
            float qq = 0.f;
#pragma unroll
            for (int i = 0; i < 8; i++) qq = fmaf(dv[t][i], dv[t][i], qq);
            if (t < 4 || v4) q += qq;
          }
          q += __shfl_xor_sync(~0u, q, 1); q += __shfl_xor_sync(~0u, q, 2); q += __shfl_xor_sync(~0u, q, 8); q += __shfl_xor_sync(~0u, q, 16);
          const float rs = rsqrtf(q * (1.f / DM) + 1e-5f);
          uint4* dst = g_hnT + ((size_t)rb * 9 + (uq >> 1)) * 1024 + (r8 & 15) * 64 + ((uq & 1) * 4 + j) * 8 + g;
#pragma unroll
          for (int t = 0; t < 5; t++)
            if (t < 4 || v4)
              stg128(dst + t * 2048, pack2(dv[t][0] * rs, dv[t][1] * rs), pack2(dv[t][2] * rs, dv[t][3] * rs),
                     pack2(dv[t][4] * rs, dv[t][5] * rs), pack2(dv[t][6] * rs, dv[t][7] * rs));
          __syncwarp();
          if (lane == 0) red_release(&g_cntH[rb * PAD]);
        }
        if (lane == 0 && (r2 & 3) == 0) TR_LOG((7 + fin) | ((r8 & 15) << 8) | (rb << 24), tr0, tr0);
      }
      if (lane == 0) finish(epoch);
      __syncwarp();
      asm volatile("barrier.cluster.arrive.relaxed.aligned; barrier.cluster.wait.aligned;" ::: "memory");
    }
  } else {
    asm volatile("setmaxnreg.inc.sync.aligned.u32 %0;" :: "n"(REG_C));
    const int g = lane >> 2, j = lane & 3;
    const int l0 = __shfl_sync(~0u, lane == 0, lane);
    for (int seq = wg;; seq += 2) {
      mbar_wait(bar + B_D + (seq & 3) * 8, (seq >> 2) & 1, t0);
      uint2 d = lds64(sb + SM_DESC + (seq & 3) * 16);
      d.x = __shfl_sync(~0u, d.x, 0); d.y = __shfl_sync(~0u, d.y, 0);
      const int type = d.x & 255;
      const int sl = (d.x >> 8) & 255, kc = (d.x >> 16) & 255, rb = d.x >> 24;
      const int nkb = task_nkb(type, kc);
      const int last = (d.y >> 16) & 1; const bool needb = (d.y >> 17) & 1;
      int st = d.y & 255, ph = ((d.y >> 8) & 1) ^ 1, prev = 0;
      float acc[2][64];
      {
        const uint32_t* bp = reinterpret_cast<const uint32_t*>(b1 + sl * 128) + j;
#pragma unroll
        for (int i = 0; i < 16; i++) {
          uint32_t b = 0;
          if (type == T_F1) b = ldg32(bp + i * 4);
          acc[0][4 * i] = acc[0][4 * i + 2] = acc[1][4 * i] = acc[1][4 * i + 2] = bflo(b);
          acc[0][4 * i + 1] = acc[0][4 * i + 3] = acc[1][4 * i + 1] = acc[1][4 * i + 3] = bfhi(b);
        }
      }
      fence_regs(acc[0]); fence_regs(acc[1]);
      if (seq > 0) bar_sync(3 + wg, 256);
      if (type == T_END) { if (d.y == 0) bar_arrive(3 + (wg ^ 1), 256); break; }
      TR_T(tr0);
      auto mainloop = [&](auto mode) {
        constexpr int MD = decltype(mode)::value;
        constexpr int PER = MD == 2 ? 4 : 3;
        const uint64_t a_hi = make_desc(0, 128, type == T_QA ? 2048 : 1024, 0), b_hi = MD == 2 ? make_desc(0, 16384, 512, 2) : make_desc(0, 24576, 1024, 1);
        const uint32_t a_off = type == T_QA ? 64 : 512;
        bool oka = false;
        int eb = 0, ec = 0;
        int bt = 0, bk = 0;
        for (int kb = 0; kb < nkb; kb++) {
          if (needb && bk == 0) mbar_wait(bar + B_FB + bt * 8, (d.y >> 18) & 1, t0);
          if (!oka) mbar_wait(bar + B_FA + st * 8, ph, t0);
          const uint64_t da = a_hi + ((((sb + SM_A) & 0x3FFFF) >> 4) + st * 1024), db = b_hi + ((((sb + SM_B) & 0x3FFFF) >> 4) + bt * 3072 + bk * (MD == 2 ? 256 : 512));
          if (++bk == PER) { bk = 0; bt++; }
          int nst = st + 1, nph = ph;
          if (nst == NS) { nst = 0; nph ^= 1; }
          wg_fence();
#pragma unroll
          for (int ks = 0; ks < 4; ks++) {
            if (MD == 1) {
              wgmma_n128<1, 0>(acc[0], db + ks * 128, da + ks * 16, 1);
              wgmma_n128<1, 0>(acc[1], db + 1536 + ks * 128, da + ks * 16, 1);
            } else if (MD == 0) {
              wgmma_n128<0, 1>(acc[0], da + ks * 16, db + ks * 128, 1);
              wgmma_n128<0, 1>(acc[1], da + a_off + ks * 16, db + ks * 128, 1);
            } else {
              wgmma_n96<0, 1>(acc[0], da + ks * 16, db + ks * 64, 1);
              wgmma_n96<0, 1>(acc[1], da + 512 + ks * 16, db + ks * 64, 1);
            }
            if (ks == 0) {
              wg_commit();
              wg_wait<1>();
              arrive2_if(bar + B_EA + prev * 8, pd, l0 & (kb > 0), 1);
              mbar_arrive_if(bar + B_EB + eb * 8, l0 & (ec == PER) & last);
              if (ec == PER) { ec = 0; eb++; }
              ec++;
              wg_fence();
            }
            if (ks == 2) {
              if (kb == nkb - 1) { oka = false; if (type != T_QA) bar_arrive(3 + (wg ^ 1), 256); }
              else oka = mbar_try(bar + B_FA + nst * 8, nph);
              wg_fence();
            }
          }
          wg_commit();
          prev = st; st = nst; ph = nph;
        }
        wg_wait<0>();
      };
      if (type == T_V) mainloop(IntC<1>()); else if (type == T_OP || type == T_F2) mainloop(IntC<2>()); else mainloop(IntC<0>());
      arrive2_if(bar + B_EA + prev * 8, pd, l0, 1);
      mbar_arrive_if(bar + B_EB + 16, l0 & last);
      fence_regs(acc[0]); fence_regs(acc[1]);
      TR_T(tr1);
      unsigned* cnt;
      if (type <= T_V) {
        uint4* base = type == T_V ? g_Vf + (((size_t)sl * NSEG + rb * 4) * 8 + w) * 64 + lane : g_Kf + ((size_t)sl * 128 + rb * 8 + w) * 256 + lane;
        const int smb = type == T_V ? 256 : 1024, sq2 = type == T_V ? 512 : 64;
#pragma unroll
        for (int mb = 0; mb < 2; mb++) {
#pragma unroll
          for (int q = 0; q < 8; q++) {
            const float* c = &acc[mb][q * 8];
            stg128(base + mb * smb + (q >> 1) * sq2 + (q & 1) * 32, pack2(c[0], c[1]), pack2(c[2], c[3]), pack2(c[4], c[5]), pack2(c[6], c[7]));
          }
        }
        cnt = &g_kvflag[rb * 64 + type * 32 + sl];
      } else if (type == T_OP || type == T_F2) {
        uint4* base = (type == T_OP ? g_p1 : g_p2) + (((size_t)(rb * 16 + w * 2) * 18 + sl * 3) * SPL + kc) * 32 + lane;
#pragma unroll
        for (int u = 0; u < 3; u++)
#pragma unroll
          for (int mb = 0; mb < 2; mb++)
#pragma unroll
            for (int hi = 0; hi < 2; hi++) {
              const float* c = &acc[mb][u * 16 + hi * 2];
              stg128(base + ((mb * 8 + hi) * 18 + u) * (SPL * 32), pack2(c[0], c[1]), pack2(c[4], c[5]), pack2(c[8], c[9]), pack2(c[12], c[13]));
            }
        cnt = type == T_OP ? &g_cntP1[(rb) * PAD] : &g_cntP2[(rb) * PAD];
      } else if (type == T_F1) {
        uint4* base = g_gT + ((size_t)rb * 72 + sl * 2) * 1024 + w * 128 + j * 8 + g;
#pragma unroll
        for (int u = 0; u < 4; u++) {
#pragma unroll
          for (int mb = 0; mb < 2; mb++) {
#pragma unroll
            for (int hi = 0; hi < 2; hi++) {
              uint32_t p[4];
#pragma unroll
              for (int i = 0; i < 4; i++) {
                const float* c = &acc[mb][(u * 4 + i) * 4 + hi * 2];
                p[i] = pack2(gelu_tanh(c[0]), gelu_tanh(c[1]));
              }
              stg128(base + (u >> 1) * 1024 + (mb * 8 + hi) * 64 + (u & 1) * 32, p[0], p[1], p[2], p[3]);
            }
          }
        }
        cnt = &g_cntG[(rb * 8 + sl / 6) * PAD];
      } else {
        uint32_t qa[2][8][4];
#pragma unroll
        for (int mb = 0; mb < 2; mb++)
#pragma unroll
          for (int ks = 0; ks < 8; ks++)
#pragma unroll
            for (int i = 0; i < 4; i++) qa[mb][ks][i] = pack2(acc[mb][ks * 8 + 2 * i], acc[mb][ks * 8 + 2 * i + 1]);
        float sc[2][5][4];
#pragma unroll
        for (int mb = 0; mb < 2; mb++)
#pragma unroll
          for (int n = 0; n < 5; n++) { sc[mb][n][0] = sc[mb][n][1] = sc[mb][n][2] = sc[mb][n][3] = 0.f; }
        auto stg_i = [&](int e) { const int q = st + e; return q >= NS ? q - NS : q; };
        auto stg_p = [&](int e) { return st + e >= NS ? ph ^ 1 : ph; };
        const int ek = w >> 1;
        const int em = (d.y >> 19) & 1 ? 2 : 4, ev = (em == 2 ? 3 : 2) + ek;
        const uint32_t woff = sb + SM_A + (w & 1) * 8192 + lane * 16;
        {
          mbar_wait(bar + B_FA + stg_i(ek) * 8, stg_p(ek), t0);
          const uint32_t ka = woff + stg_i(ek) * 16384;
          uint4 kf[16];
#pragma unroll
          for (int i = 0; i < 16; i++) kf[i] = lds128(ka + i * 512);
#pragma unroll
          for (int ks = 0; ks < 8; ks++) {
#pragma unroll
            for (int mb = 0; mb < 2; mb++) {
              mma16816(sc[mb][0], qa[mb][ks], kf[ks].x, kf[ks].z);
              mma16816(sc[mb][1], qa[mb][ks], kf[ks].y, kf[ks].w);
              mma16816(sc[mb][2], qa[mb][ks], kf[8 + ks].x, kf[8 + ks].z);
              if (mb == 1) mma16816(sc[mb][3], qa[mb][ks], kf[8 + ks].y, kf[8 + ks].w);
            }
          }
          __syncwarp();
          arrive2_if(bar + B_EA + stg_i(ek) * 8, pd, l0, 2);
        }
        uint4 vf[16], km[4], vm[4];
        TR_T(tq0);
        {
          mbar_wait(bar + B_FA + stg_i(em) * 8, stg_p(em), t0);
          const uint32_t ma = sb + SM_A + stg_i(em) * 16384 + w * 2048 + lane * 16;
#pragma unroll
          for (int i = 0; i < 4; i++) km[i] = lds128(ma + i * 512);
          float s2[2][4] = {{0.f, 0.f, 0.f, 0.f}, {0.f, 0.f, 0.f, 0.f}};
#pragma unroll
          for (int u = 0; u < 4; u++) {
#pragma unroll
            for (int mb = 0; mb < 2; mb++) {
              mma16816(sc[mb][4], qa[mb][2 * u], km[u].x, km[u].y);
              mma16816(s2[mb], qa[mb][2 * u + 1], km[u].z, km[u].w);
            }
          }
#pragma unroll
          for (int mb = 0; mb < 2; mb++)
#pragma unroll
            for (int i = 0; i < 4; i++) sc[mb][4][i] += s2[mb][i];
#pragma unroll
          for (int i = 0; i < 4; i++) vm[i] = lds128(ma + 8192 + i * 512);
        }
        const float scl = 0.08838834764831845f * 1.4426950408889634f;
        const float NEG = -INFINITY;
        uint32_t pa[2][5][2];
        float inv[2][2];
#pragma unroll
        for (int mb = 0; mb < 2; mb++) {
#pragma unroll
          for (int hi = 0; hi < 2; hi++) {
            const int nd = mb + 2 * hi;
            if (2 * j > g) sc[mb][nd][hi * 2] = NEG;
            if (2 * j + 1 > g) sc[mb][nd][hi * 2 + 1] = NEG;
            float m = fmaxf(sc[mb][4][hi * 2], sc[mb][4][hi * 2 + 1]);
#pragma unroll
            for (int n = 0; n < 4; n++) if (n <= nd) m = fmaxf(m, fmaxf(sc[mb][n][hi * 2], sc[mb][n][hi * 2 + 1]));
            m = fmaxf(m, __shfl_xor_sync(~0u, m, 1)); m = fmaxf(m, __shfl_xor_sync(~0u, m, 2));
            const float mc = m * scl;
            float l = 0.f;
#pragma unroll
            for (int n = 0; n < 5; n++) {
              if (n <= nd || n == 4) {
                const float e0 = ex2(fmaf(sc[mb][n][hi * 2], scl, -mc)), e1 = ex2(fmaf(sc[mb][n][hi * 2 + 1], scl, -mc));
                l += e0 + e1;
                pa[mb][n][hi] = pack2(e0, e1);
              } else pa[mb][n][hi] = 0u;
            }
            l += __shfl_xor_sync(~0u, l, 1); l += __shfl_xor_sync(~0u, l, 2);
            inv[mb][hi] = __fdividef(1.f, l);
          }
        }
        {
          mbar_wait(bar + B_FA + stg_i(ev) * 8, stg_p(ev), t0);
          const uint32_t va = woff + stg_i(ev) * 16384;
#pragma unroll
          for (int i = 0; i < 16; i++) vf[i] = lds128(va + i * 512);
        }
        asm volatile("" :: "r"(vm[3].w), "r"(vf[15].w) : "memory");
        __syncwarp();
        arrive2_if(bar + B_EA + stg_i(ev) * 8, pd, l0, 2);
        arrive2_if(bar + B_EA + stg_i(em) * 8, pd, l0, 1);
        TR_T(tq1);
        uint32_t op[4][2][2][4];
        uint4* obase = g_oT + ((size_t)rb * 64 + sl * 2) * 1024 + w * 256 + j * 8 + g;
#pragma unroll
        for (int u = 0; u < 4; u++) {
          float o[2][4][4];
#pragma unroll
          for (int mb = 0; mb < 2; mb++) {
#pragma unroll
            for (int i = 0; i < 4; i++) {
              o[mb][i][0] = o[mb][i][1] = o[mb][i][2] = o[mb][i][3] = 0.f;
              const uint4 v0 = vf[(2 * u + (i >> 1)) * 2], v1 = vf[(2 * u + (i >> 1)) * 2 + 1];
              const uint32_t vmw = i == 0 ? vm[u].x : i == 1 ? vm[u].y : i == 2 ? vm[u].z : vm[u].w;
              mma1688(o[mb][i], pa[mb][4][0], pa[mb][4][1], vmw);
              mma16816(o[mb][i], pa[mb][0][0], pa[mb][0][1], pa[mb][1][0], pa[mb][1][1], (i & 1) ? v0.y : v0.x, (i & 1) ? v0.w : v0.z);
              if (mb == 0) mma1688(o[mb][i], pa[mb][2][0], pa[mb][2][1], (i & 1) ? v1.y : v1.x);
              else mma16816(o[mb][i], pa[mb][2][0], pa[mb][2][1], pa[mb][3][0], pa[mb][3][1], (i & 1) ? v1.y : v1.x, (i & 1) ? v1.w : v1.z);
            }
          }
          if (u == 3) bar_arrive(3 + (wg ^ 1), 256);
#pragma unroll
          for (int mb = 0; mb < 2; mb++) {
#pragma unroll
            for (int hi = 0; hi < 2; hi++) {
              const float s = inv[mb][hi];
#pragma unroll
              for (int i = 0; i < 4; i++) op[u][mb][hi][i] = pack2(o[mb][i][hi * 2] * s, o[mb][i][hi * 2 + 1] * s);
            }
          }
        }
        TR_T(tq2);
#pragma unroll
        for (int u = 0; u < 4; u++)
#pragma unroll
          for (int mb = 0; mb < 2; mb++)
#pragma unroll
            for (int hi = 0; hi < 2; hi++)
              stg128(obase + (u >> 1) * 1024 + (mb + 2 * hi) * 64 + (u & 1) * 32, op[u][mb][hi][0], op[u][mb][hi][1], op[u][mb][hi][2], op[u][mb][hi][3]);
        if (tid == wg * 128) TR_LOG(10 | (rb << 24), tq0 - tr1, tq1 - tr1);
        if (tid == wg * 128) TR_LOG(11 | (rb << 24), tq2 - tr1, tr1);
        cnt = &g_cntO[(rb * 8 + (sl < 12 ? sl / 6 : 2 + (sl - 12) / 5)) * PAD];
      }
      mbar_wait(bar + B_PE + wg * 8, ((seq >> 1) & 1) ^ 1, t0);
      if (w == 0 && l0) {
        sts64(sb + SM_PUB + wg * 8, (uint32_t)(uintptr_t)cnt, (uint32_t)((uintptr_t)cnt >> 32));
        TR_LOG(d.x, tr0, tr1);
      }
      __syncwarp();
      mbar_arrive_if(bar + B_PD + wg * 8, l0);
    }
    __syncwarp();
    asm volatile("barrier.cluster.arrive.relaxed.aligned; barrier.cluster.wait.aligned;" ::: "memory");
  }
}
}
typedef CUresult (*EncodeFn)(CUtensorMap*, CUtensorMapDataType, cuuint32_t, void*, const cuuint64_t*, const cuuint64_t*, const cuuint32_t*,
                             const cuuint32_t*, CUtensorMapInterleave, CUtensorMapSwizzle, CUtensorMapL2promotion, CUtensorMapFloatOOBfill);
static EncodeFn get_encode() {
  void* fn = nullptr; cudaDriverEntryPointQueryResult st;
  cudaGetDriverEntryPoint("cuTensorMapEncodeTiled", &fn, cudaEnableDefault, &st);
  return (EncodeFn)fn;
}
static CUtensorMap map2d(EncodeFn enc, const void* p, int rows, int cols, int brow) {
  CUtensorMap m;
  cuuint64_t dim[2] = {(cuuint64_t)cols, (cuuint64_t)rows}; cuuint64_t str[1] = {(cuuint64_t)cols * 2};
  cuuint32_t box[2] = {64, (cuuint32_t)brow}, es[2] = {1, 1};
  enc(&m, CU_TENSOR_MAP_DATA_TYPE_BFLOAT16, 2, (void*)p, dim, str, box, es, CU_TENSOR_MAP_INTERLEAVE_NONE, CU_TENSOR_MAP_SWIZZLE_128B,
      CU_TENSOR_MAP_L2_PROMOTION_L2_256B, CU_TENSOR_MAP_FLOAT_OOB_FILL_NONE);
  return m;
}
static CUtensorMap map5d(EncodeFn enc, const void* p, int rows, int cols, int bcols) {
  CUtensorMap m;
  const cuuint64_t rs = (cuuint64_t)cols * 2;
  cuuint64_t dim[5] = {(cuuint64_t)cols, 2, 4, 4, (cuuint64_t)rows / 32}; cuuint64_t str[4] = {rs, 8 * rs, 2 * rs, 32 * rs};
  cuuint32_t box[5] = {(cuuint32_t)bcols, 2, 4, 4, bcols == 64 ? 6u : 8u}, es[5] = {1, 1, 1, 1, 1};
  enc(&m, CU_TENSOR_MAP_DATA_TYPE_BFLOAT16, 5, (void*)p, dim, str, box, es, CU_TENSOR_MAP_INTERLEAVE_NONE,
      bcols == 64 ? CU_TENSOR_MAP_SWIZZLE_128B : CU_TENSOR_MAP_SWIZZLE_64B,
      CU_TENSOR_MAP_L2_PROMOTION_L2_256B, CU_TENSOR_MAP_FLOAT_OOB_FILL_NONE);
  return m;
}
static CUtensorMap map3d(EncodeFn enc, const void* p, int brows) {
  CUtensorMap m;
  cuuint64_t dim[3] = {64, (cuuint64_t)DM, HD / 64}; cuuint64_t str[2] = {(cuuint64_t)HD * 2, 128};
  cuuint32_t box[3] = {64, (cuuint32_t)brows, 2}, es[3] = {1, 1, 1};
  enc(&m, CU_TENSOR_MAP_DATA_TYPE_BFLOAT16, 3, (void*)p, dim, str, box, es, CU_TENSOR_MAP_INTERLEAVE_NONE, CU_TENSOR_MAP_SWIZZLE_128B,
      CU_TENSOR_MAP_L2_PROMOTION_L2_256B, CU_TENSOR_MAP_FLOAT_OOB_FILL_NONE);
  return m;
}
template <typename... KArgs, typename... Args>
static void launch(void (*k)(KArgs...), int grid, int block, int smem, cudaStream_t s, int cluster, bool pdl, Args... args) {
  cudaLaunchConfig_t cfg = {};
  cfg.gridDim = dim3(grid); cfg.blockDim = dim3(block); cfg.dynamicSmemBytes = smem; cfg.stream = s;
  cudaLaunchAttribute at[2]; int n = 0;
  if (cluster > 1) { at[n].id = cudaLaunchAttributeClusterDimension; at[n].val.clusterDim.x = cluster; at[n].val.clusterDim.y = 1; at[n].val.clusterDim.z = 1; n++; }
  if (pdl) { at[n].id = cudaLaunchAttributeProgrammaticStreamSerialization; at[n].val.programmaticStreamSerializationAllowed = 1; n++; }
  cfg.attrs = at; cfg.numAttrs = n;
  cudaLaunchKernelEx(&cfg, k, KArgs(args)...);
}
struct Ctx {
  mega::Maps maps;
  chain::Maps cmaps;
  cudaStream_t s2; cudaEvent_t evFork, evJoin;
  bool init;
};
static void setup(Ctx& c, void* const* d_in) {
  EncodeFn enc = get_encode();
  c.maps.m[mega::T_K] = map3d(enc, d_in[3], 192); c.maps.m[mega::T_V] = map3d(enc, d_in[4], 192);
  c.maps.m[mega::T_QA] = map3d(enc, d_in[2], 192);
  c.maps.m[mega::T_OP] = map5d(enc, d_in[5], HD, DM, 32); c.maps.m[mega::T_F1] = map5d(enc, d_in[8], DM, FF, 64); c.maps.m[mega::T_F2] = map5d(enc, d_in[10], FF, DM, 32);
  c.cmaps.q = map3d(enc, d_in[2], 16); c.cmaps.k = map3d(enc, d_in[3], 16); c.cmaps.v = map3d(enc, d_in[4], 16); c.cmaps.o = map2d(enc, d_in[5], HD, DM, 128);
  cudaFuncSetAttribute(chain::chain_kernel, cudaFuncAttributeNonPortableClusterSizeAllowed, 1);
  cudaFuncSetAttribute(chain::chain_kernel, cudaFuncAttributeMaxDynamicSharedMemorySize, chain::SM_TOTAL);
  cudaFuncSetAttribute(mega::mega_kernel, cudaFuncAttributeMaxDynamicSharedMemorySize, mega::SM_TOTAL);
  cudaFuncAttributes fa;
  cudaFuncGetAttributes(&fa, gate_kernel);
  int lo, hi; cudaDeviceGetStreamPriorityRange(&lo, &hi);
  cudaStreamCreateWithPriority(&c.s2, cudaStreamNonBlocking, hi);
  cudaEventCreateWithFlags(&c.evFork, cudaEventDisableTiming); cudaEventCreateWithFlags(&c.evJoin, cudaEventDisableTiming);
  c.init = true;
}
static Ctx g_ctx;
extern "C" void kernel_launch(void* const* d_in, const int* in_sizes, int n_in, void* d_out, int out_size) {
  Ctx& c = g_ctx;
  if (!c.init) setup(c, d_in);
  const bf16 *x = (const bf16*)d_in[0], *mem0 = (const bf16*)d_in[1], *b1 = (const bf16*)d_in[9], *b2 = (const bf16*)d_in[11];
  bf16* out = (bf16*)d_out;
  cudaStream_t s = cudaStreamPerThread;
  cudaEventRecord(c.evFork, s);
  cudaStreamWaitEvent(c.s2, c.evFork, 0);
  launch(chain::chain_kernel, 64, chain::NTHREADS, chain::SM_TOTAL, c.s2, 16, false, c.cmaps, mem0, x, (const bf16*)d_in[2], (const bf16*)d_in[3], (const bf16*)d_in[4], (const bf16*)d_in[5], 0u);
  cudaEventRecord(c.evJoin, c.s2);
  launch(gate_kernel, 1, 1, 0, s, 1, false);
  launch(mega::mega_kernel, 132, 384, mega::SM_TOTAL, s, 2, true, c.maps, x, b1, b2, out);
  cudaStreamWaitEvent(s, c.evJoin, 0);
}
```

```cpp
#include <cuda_runtime.h>
#include <cuda_bf16.h>
#include <cuda.h>
#include <stdint.h>

typedef __nv_bfloat16 bf16;

constexpr int SEQ = 2048, DM = 576, NH = 32, DH = 128, HD = 4096, FF = 4608, NSEG = 64, NRB = 16;

__device__ __align__(1024) uint4 g_Kf[NH * 256 * 4 * 32];
__device__ __align__(1024) uint4 g_Vf[NH * NSEG * 128 * 4];
__device__ __align__(1024) uint4 g_Kmf[NH * NSEG * 4 * 32];
__device__ __align__(1024) uint4 g_Vmf[NH * NSEG * 4 * 32];
__device__ __align__(8192) uint4 g_xch[65 * 512];
__device__ unsigned g_kvflag[NRB * 64];
__device__ unsigned g_memflag[NH * 8];
__device__ __align__(1024) uint4 g_xnT[NRB * 9 * 1024];
__device__ unsigned g_cntX[NRB * 32];
__device__ unsigned g_prog;
__device__ unsigned g_epoch;
__device__ unsigned g_resident;
__device__ unsigned g_err;

__device__ __forceinline__ uint32_t smem_u32(const void* p) { return (uint32_t)__cvta_generic_to_shared(p); }
__device__ __forceinline__ void mbar_init(uint32_t a, int cnt) { asm volatile("mbarrier.init.shared::cta.b64 [%0], %1;" :: "r"(a), "r"(cnt) : "memory"); }
__device__ __forceinline__ void mbar_expect(uint32_t a, int bytes) { asm volatile("mbarrier.arrive.expect_tx.shared::cta.b64 _, [%0], %1;" :: "r"(a), "r"(bytes) : "memory"); }
__device__ __forceinline__ void mbar_arrive(uint32_t a) { asm volatile("mbarrier.arrive.shared::cta.b64 _, [%0];" :: "r"(a) : "memory"); }
__device__ __forceinline__ void mbar_arrive_if(uint32_t a, int p) { asm volatile("{ .reg .pred q; setp.ne.b32 q, %1, 0; @q mbarrier.arrive.shared::cta.b64 _, [%0]; }" :: "r"(a), "r"(p) : "memory"); }
__device__ __forceinline__ bool mbar_try(uint32_t a, uint32_t parity) {
  uint32_t ok;
  asm volatile("{ .reg .pred p; mbarrier.try_wait.parity.shared::cta.b64 p, [%1], %2; selp.u32 %0, 1, 0, p; }" : "=r"(ok) : "r"(a), "r"(parity) : "memory");
  return ok;
}
__device__ __forceinline__ bool mbar_test(uint32_t a, uint32_t parity) {
  uint32_t ok;
  asm volatile("{ .reg .pred p; mbarrier.test_wait.parity.shared::cta.b64 p, [%1], %2; selp.u32 %0, 1, 0, p; }" : "=r"(ok) : "r"(a), "r"(parity) : "memory");
  return ok;
}
__device__ __forceinline__ bool mbar_try_cl(uint32_t a, uint32_t parity) {
  uint32_t ok;
  asm volatile("{ .reg .pred p; mbarrier.try_wait.parity.acquire.cluster.shared::cta.b64 p, [%1], %2; selp.u32 %0, 1, 0, p; }" : "=r"(ok) : "r"(a), "r"(parity) : "memory");
  return ok;
}
__device__ __forceinline__ uint32_t clk32() { uint32_t c; asm volatile("mov.u32 %0, %%clock;" : "=r"(c)); return c; }
constexpr uint32_t TIMEOUT_CLKS = 400000000u;
__device__ __forceinline__ bool timed_out(uint32_t t0) {
  if (clk32() - t0 > TIMEOUT_CLKS) { g_err = 1; return true; }
  return false;
}
__device__ __forceinline__ void mbar_wait(uint32_t a, uint32_t parity, uint32_t t0) {
  if (mbar_try(a, parity)) return;
  while (!mbar_try(a, parity)) { if (timed_out(t0)) break; }
}
__device__ __forceinline__ void mbar_wait_cl(uint32_t a, uint32_t parity, uint32_t t0) {
  while (!mbar_try_cl(a, parity)) { if (timed_out(t0)) break; }
}
__device__ __forceinline__ uint32_t mapa(uint32_t a, uint32_t r) { uint32_t d; asm volatile("mapa.shared::cluster.u32 %0, %1, %2;" : "=r"(d) : "r"(a), "r"(r)); return d; }
__device__ __forceinline__ void st_async16(uint32_t a, uint32_t x, uint32_t y, uint32_t z, uint32_t w, uint32_t bar) {
  asm volatile("st.async.shared::cluster.mbarrier::complete_tx::bytes.v4.b32 [%0], {%1,%2,%3,%4}, [%5];" :: "r"(a), "r"(x), "r"(y), "r"(z), "r"(w), "r"(bar) : "memory");
}
__device__ __forceinline__ void st_async8(uint32_t a, uint32_t x, uint32_t y, uint32_t bar) {
  asm volatile("st.async.shared::cluster.mbarrier::complete_tx::bytes.v2.b32 [%0], {%1,%2}, [%3];" :: "r"(a), "r"(x), "r"(y), "r"(bar) : "memory");
}
__device__ __forceinline__ void bar_sync(int id, int n) { asm volatile("bar.sync %0, %1;" :: "r"(id), "r"(n) : "memory"); }
__device__ __forceinline__ void bar_arrive(int id, int n) { asm volatile("bar.arrive %0, %1;" :: "r"(id), "r"(n) : "memory"); }
__device__ __forceinline__ void cluster_sync() { asm volatile("barrier.cluster.arrive.release.aligned; barrier.cluster.wait.acquire.aligned;" ::: "memory"); }
__device__ __forceinline__ uint32_t pack2(float lo, float hi) { uint32_t d; asm("cvt.rn.bf16x2.f32 %0, %1, %2;" : "=r"(d) : "f"(hi), "f"(lo)); return d; }
__device__ __forceinline__ float bflo(uint32_t v) { return __uint_as_float(v << 16); }
__device__ __forceinline__ float bfhi(uint32_t v) { return __uint_as_float(v & 0xffff0000u); }
__device__ __forceinline__ uint32_t movmat(uint32_t a) { uint32_t d; asm volatile("movmatrix.sync.aligned.m8n8.trans.b16 %0, %1;" : "=r"(d) : "r"(a)); return d; }
__device__ __forceinline__ uint32_t hadd2bf(uint32_t a, uint32_t b) { uint32_t d; asm("add.rn.bf16x2 %0, %1, %2;" : "=r"(d) : "r"(a), "r"(b)); return d; }
__device__ __forceinline__ void mma16816(float (&c)[4], uint32_t a0, uint32_t a1, uint32_t a2, uint32_t a3, uint32_t b0, uint32_t b1) {
  asm volatile("mma.sync.aligned.m16n8k16.row.col.f32.bf16.bf16.f32 {%0,%1,%2,%3}, {%4,%5,%6,%7}, {%8,%9}, {%0,%1,%2,%3};"
    : "+f"(c[0]), "+f"(c[1]), "+f"(c[2]), "+f"(c[3]) : "r"(a0), "r"(a1), "r"(a2), "r"(a3), "r"(b0), "r"(b1));
}
__device__ __forceinline__ void mma16816(float (&c)[4], const uint32_t (&a)[4], uint32_t b0, uint32_t b1) { mma16816(c, a[0], a[1], a[2], a[3], b0, b1); }
__device__ __forceinline__ void mma1688(float (&c)[4], uint32_t a0, uint32_t a1, uint32_t b0) {
  asm volatile("mma.sync.aligned.m16n8k8.row.col.f32.bf16.bf16.f32 {%0,%1,%2,%3}, {%4,%5}, {%6}, {%0,%1,%2,%3};"
    : "+f"(c[0]), "+f"(c[1]), "+f"(c[2]), "+f"(c[3]) : "r"(a0), "r"(a1), "r"(b0));
}
__device__ __forceinline__ void ldsm4t(uint32_t (&r)[4], uint32_t a) {
  asm volatile("ldmatrix.sync.aligned.m8n8.x4.trans.shared.b16 {%0,%1,%2,%3}, [%4];" : "=r"(r[0]), "=r"(r[1]), "=r"(r[2]), "=r"(r[3]) : "r"(a) : "memory");
}
__device__ __forceinline__ uint4 lds128(uint32_t a) { uint4 v; asm volatile("ld.shared.v4.b32 {%0,%1,%2,%3}, [%4];" : "=r"(v.x), "=r"(v.y), "=r"(v.z), "=r"(v.w) : "r"(a) : "memory"); return v; }
__device__ __forceinline__ uint2 lds64(uint32_t a) { uint2 v; asm volatile("ld.shared.v2.b32 {%0,%1}, [%2];" : "=r"(v.x), "=r"(v.y) : "r"(a) : "memory"); return v; }
__device__ __forceinline__ void sts128(uint32_t a, uint32_t x, uint32_t y, uint32_t z, uint32_t w) { asm volatile("st.shared.v4.b32 [%0], {%1,%2,%3,%4};" :: "r"(a), "r"(x), "r"(y), "r"(z), "r"(w) : "memory"); }
__device__ __forceinline__ void sts64(uint32_t a, uint32_t x, uint32_t y) { asm volatile("st.shared.v2.b32 [%0], {%1,%2};" :: "r"(a), "r"(x), "r"(y) : "memory"); }
__device__ __forceinline__ void sts32(uint32_t a, uint32_t x) { asm volatile("st.shared.b32 [%0], %1;" :: "r"(a), "r"(x) : "memory"); }
__device__ __forceinline__ void cp_async16(uint32_t dst, const void* src) { asm volatile("cp.async.cg.shared.global [%0], [%1], 16;" :: "r"(dst), "l"(src) : "memory"); }
__device__ __forceinline__ void cp_async_wait_all() { asm volatile("cp.async.wait_all;" ::: "memory"); }
__device__ __forceinline__ uint4 ldg_cg(const void* p) { uint4 v; asm volatile("ld.global.cg.v4.b32 {%0,%1,%2,%3}, [%4];" : "=r"(v.x), "=r"(v.y), "=r"(v.z), "=r"(v.w) : "l"(p) : "memory"); return v; }
__device__ __forceinline__ uint4 ld_relaxed16(const void* p) { uint4 v; asm volatile("ld.relaxed.gpu.global.v4.b32 {%0,%1,%2,%3}, [%4];" : "=r"(v.x), "=r"(v.y), "=r"(v.z), "=r"(v.w) : "l"(p) : "memory"); return v; }
__device__ __forceinline__ void st_relaxed16(void* p, uint32_t x, uint32_t y, uint32_t z, uint32_t w) { asm volatile("st.relaxed.gpu.global.v4.b32 [%0], {%1,%2,%3,%4};" :: "l"(p), "r"(x), "r"(y), "r"(z), "r"(w) : "memory"); }
__device__ __forceinline__ unsigned ld_acquire(const unsigned* p) { unsigned v; asm volatile("ld.acquire.gpu.global.u32 %0, [%1];" : "=r"(v) : "l"(p) : "memory"); return v; }
__device__ __forceinline__ uint32_t ldg32(const void* p) { uint32_t v; asm volatile("ld.global.nc.b32 %0, [%1];" : "=r"(v) : "l"(p)); return v; }
__device__ __forceinline__ uint2 ld_relaxed8(const unsigned* p) { uint2 v; asm volatile("ld.relaxed.gpu.global.v2.u32 {%0,%1}, [%2];" : "=r"(v.x), "=r"(v.y) : "l"(p) : "memory"); return v; }
__device__ __forceinline__ unsigned ld_relaxed(const unsigned* p) { unsigned v; asm volatile("ld.relaxed.gpu.global.u32 %0, [%1];" : "=r"(v) : "l"(p) : "memory"); return v; }
__device__ __forceinline__ void st_release(unsigned* p, unsigned v) { asm volatile("st.release.gpu.global.u32 [%0], %1;" :: "l"(p), "r"(v) : "memory"); }
__device__ __forceinline__ float ex2(float x) { float y; asm("ex2.approx.ftz.f32 %0, %1;" : "=f"(y) : "f"(x)); return y; }

__device__ __forceinline__ void st_b128(void* p, uint32_t x, uint32_t y, uint32_t z, uint32_t w) {
  asm volatile("{ .reg .b128 t; .reg .b64 lo, hi; mov.b64 lo, {%1,%2}; mov.b64 hi, {%3,%4}; mov.b128 t, {lo,hi}; st.relaxed.gpu.global.b128 [%0], t; }"
    :: "l"(p), "r"(x), "r"(y), "r"(z), "r"(w) : "memory");
}
__device__ __forceinline__ uint4 ld_b128(const void* p) {
  uint4 v;
  asm volatile("{ .reg .b128 t; .reg .b64 lo, hi; ld.relaxed.gpu.global.b128 t, [%4]; mov.b128 {lo,hi}, t; mov.b64 {%0,%1}, lo; mov.b64 {%2,%3}, hi; }"
    : "=r"(v.x), "=r"(v.y), "=r"(v.z), "=r"(v.w) : "l"(p) : "memory");
  return v;
}
__device__ __forceinline__ void wg_fence() { asm volatile("wgmma.fence.sync.aligned;" ::: "memory"); }
__device__ __forceinline__ void wg_commit() { asm volatile("wgmma.commit_group.sync.aligned;" ::: "memory"); }
template <int N> __device__ __forceinline__ void wg_wait() { asm volatile("wgmma.wait_group.sync.aligned %0;" :: "n"(N) : "memory"); }
__device__ __forceinline__ uint64_t make_desc(uint32_t addr, uint32_t lbo, uint32_t sbo, uint32_t mode) {
  return (uint64_t)((addr & 0x3FFFF) >> 4) | ((uint64_t)(lbo >> 4) << 16) | ((uint64_t)(sbo >> 4) << 32) | ((uint64_t)mode << 62);
}
__device__ __forceinline__ void tma2d(uint32_t dst, const CUtensorMap* m, int c0, int c1, uint32_t bar) {
  asm volatile("cp.async.bulk.tensor.2d.shared::cluster.global.mbarrier::complete_tx::bytes [%0], [%1, {%3, %4}], [%2];"
    :: "r"(dst), "l"(m), "r"(bar), "r"(c0), "r"(c1) : "memory");
}
__device__ __forceinline__ bool elect() {
  uint32_t p; asm volatile("{ .reg .pred q; elect.sync _|q, 0xffffffff; selp.u32 %0, 1, 0, q; }" : "=r"(p)); return p;
}
__device__ __forceinline__ void tma3d(uint32_t dst, const CUtensorMap* m, int c1, int c2, uint32_t bar) {
  asm volatile("cp.async.bulk.tensor.3d.shared::cluster.global.mbarrier::complete_tx::bytes [%0], [%1, {%5, %3, %4}], [%2];"
    :: "r"(dst), "l"(m), "r"(bar), "r"(c1), "r"(c2), "r"(0) : "memory");
}
__device__ __forceinline__ void tma5d(uint32_t dst, const CUtensorMap* m, int c0, int c4, uint32_t bar) {
  asm volatile("cp.async.bulk.tensor.5d.shared::cluster.global.mbarrier::complete_tx::bytes [%0], [%1, {%3, %5, %5, %5, %4}], [%2];"
    :: "r"(dst), "l"(m), "r"(bar), "r"(c0), "r"(c4), "r"(0) : "memory");
}
__device__ __forceinline__ void bulk_g2s(uint32_t dst, const void* src, uint32_t bytes, uint32_t bar) {
  asm volatile("cp.async.bulk.shared::cluster.global.mbarrier::complete_tx::bytes [%0], [%1], %2, [%3];" :: "r"(dst), "l"(src), "r"(bytes), "r"(bar) : "memory");
}
__device__ __forceinline__ void push_dsmem(uint32_t dst, uint32_t src, uint32_t bytes, uint32_t bar, bool on) {
  asm volatile("fence.proxy.async.shared::cta;" ::: "memory");
  __syncwarp();
  if (on && elect())
    asm volatile("cp.async.bulk.shared::cluster.shared::cta.mbarrier::complete_tx::bytes [%0], [%1], %2, [%3];" :: "r"(dst), "r"(src), "r"(bytes), "r"(bar) : "memory");
}
__device__ __forceinline__ void stg128(void* p, uint32_t x, uint32_t y, uint32_t z, uint32_t w) {
  asm volatile("st.global.v4.b32 [%0], {%1,%2,%3,%4};" :: "l"(p), "r"(x), "r"(y), "r"(z), "r"(w) : "memory");
}
template <int N> __device__ __forceinline__ void fence_regs(float (&d)[N]) {
#pragma unroll
  for (int i = 0; i < N; i++) asm volatile("" : "+f"(d[i]) :: "memory");
}

#define TR_T(v)
#define TR_VAR(v)
#define TR_SET(v)
#define TR_LOG(info, a, b)
template <int TA, int TB>
__device__ __forceinline__ void wgmma_n96(float (&d)[64], uint64_t da, uint64_t db, int scale_d) {
  asm volatile("{ .reg .pred p; setp.ne.b32 p, %50, 0;\n"
    "wgmma.mma_async.sync.aligned.m64n96k16.f32.bf16.bf16 {%0, %1, %2, %3, %4, %5, %6, %7, %8, %9, %10, %11, %12, %13, %14, %15, %16, %17, %18, %19, %20, %21, %22, %23, %24, %25, %26, %27, %28, %29, %30, %31, %32, %33, %34, %35, %36, %37, %38, %39, %40, %41, %42, %43, %44, %45, %46, %47}, %48, %49, p, 1, 1, %51, %52; }"
    : "+f"(d[0]), "+f"(d[1]), "+f"(d[2]), "+f"(d[3]), "+f"(d[4]), "+f"(d[5]), "+f"(d[6]), "+f"(d[7]), "+f"(d[8]), "+f"(d[9]), "+f"(d[10]), "+f"(d[11]), "+f"(d[12]), "+f"(d[13]), "+f"(d[14]), "+f"(d[15]), "+f"(d[16]), "+f"(d[17]), "+f"(d[18]), "+f"(d[19]), "+f"(d[20]), "+f"(d[21]), "+f"(d[22]), "+f"(d[23]), "+f"(d[24]), "+f"(d[25]), "+f"(d[26]), "+f"(d[27]), "+f"(d[28]), "+f"(d[29]), "+f"(d[30]), "+f"(d[31]), "+f"(d[32]), "+f"(d[33]), "+f"(d[34]), "+f"(d[35]), "+f"(d[36]), "+f"(d[37]), "+f"(d[38]), "+f"(d[39]), "+f"(d[40]), "+f"(d[41]), "+f"(d[42]), "+f"(d[43]), "+f"(d[44]), "+f"(d[45]), "+f"(d[46]), "+f"(d[47])
    : "l"(da), "l"(db), "r"(scale_d), "n"(TA), "n"(TB));
}
template <int TA, int TB>
__device__ __forceinline__ void wgmma_n128(float (&d)[64], uint64_t da, uint64_t db, int scale_d) {
  asm volatile("{ .reg .pred p; setp.ne.b32 p, %66, 0;\n"
    "wgmma.mma_async.sync.aligned.m64n128k16.f32.bf16.bf16 {%0, %1, %2, %3, %4, %5, %6, %7, %8, %9, %10, %11, %12, %13, %14, %15, %16, %17, %18, %19, %20, %21, %22, %23, %24, %25, %26, %27, %28, %29, %30, %31, %32, %33, %34, %35, %36, %37, %38, %39, %40, %41, %42, %43, %44, %45, %46, %47, %48, %49, %50, %51, %52, %53, %54, %55, %56, %57, %58, %59, %60, %61, %62, %63}, %64, %65, p, 1, 1, %67, %68; }"
    : "+f"(d[0]), "+f"(d[1]), "+f"(d[2]), "+f"(d[3]), "+f"(d[4]), "+f"(d[5]), "+f"(d[6]), "+f"(d[7]), "+f"(d[8]), "+f"(d[9]), "+f"(d[10]), "+f"(d[11]), "+f"(d[12]), "+f"(d[13]), "+f"(d[14]), "+f"(d[15]), "+f"(d[16]), "+f"(d[17]), "+f"(d[18]), "+f"(d[19]), "+f"(d[20]), "+f"(d[21]), "+f"(d[22]), "+f"(d[23]), "+f"(d[24]), "+f"(d[25]), "+f"(d[26]), "+f"(d[27]), "+f"(d[28]), "+f"(d[29]), "+f"(d[30]), "+f"(d[31]), "+f"(d[32]), "+f"(d[33]), "+f"(d[34]), "+f"(d[35]), "+f"(d[36]), "+f"(d[37]), "+f"(d[38]), "+f"(d[39]), "+f"(d[40]), "+f"(d[41]), "+f"(d[42]), "+f"(d[43]), "+f"(d[44]), "+f"(d[45]), "+f"(d[46]), "+f"(d[47]), "+f"(d[48]), "+f"(d[49]), "+f"(d[50]), "+f"(d[51]), "+f"(d[52]), "+f"(d[53]), "+f"(d[54]), "+f"(d[55]), "+f"(d[56]), "+f"(d[57]), "+f"(d[58]), "+f"(d[59]), "+f"(d[60]), "+f"(d[61]), "+f"(d[62]), "+f"(d[63])
    : "l"(da), "l"(db), "r"(scale_d), "n"(TA), "n"(TB));
}
#define POLL_MODE 1
#define STAGGER 0
#define WEARLY 6
#define WLATE 1
#define PREF 0
#define CREG 216
#define AREG 72
#define KEEPALIVE 150
#define OWNMMA 0
#define WXE 4
#define PREF_M0 2
#define BULK 0
#define POLL_DELAY 120
#define STICKY 0
#define POLL_GAP 100
#define POLL_REP 1
namespace chain {
constexpr int SLOT = 4096;
constexpr int NX = 8;
constexpr int NPV = 9;
constexpr int NV2 = 18 - NPV;
constexpr int NPERM = 2 * (18 - NX) + NPV;
constexpr int SM_X = 0;
constexpr int SM_V2 = SM_X + 2 * NX * SLOT;
constexpr int SM_KX = SM_V2 + NV2 * SLOT;
constexpr int SM_VX = SM_KX + 8192;
constexpr int SM_WO = SM_VX + 8192;
static_assert(SM_WO == NPERM * SLOT, "staging area = X + V2 + KX + VX");
constexpr int SM_MEM = SM_WO + 5 * 16384;
constexpr int SM_OQK = SM_MEM + 9 * 512;
constexpr int SM_XQK = SM_OQK + 4096;
constexpr int SM_OV = SM_XQK + 4096;
constexpr int SM_XV = SM_OV + 2048;
constexpr int SM_S = SM_XV + 2048;
constexpr int SM_O = SM_S + 1536;
constexpr int SM_RS = SM_O + 2048;
constexpr int SM_MB = SM_RS + 8 * 576;
constexpr int SM_INV = SM_MB + 3 * 1152;
constexpr int SM_BAR = SM_INV + 128;
constexpr int SM_PROF = SM_BAR + 128;
constexpr int SM_TOTAL = SM_PROF + 256;
static_assert(SM_TOTAL <= 232448, "smem");
constexpr int B_AG = 0  , B_XQK = 40, B_XV = 48, B_RS = 56, B_KV = 64, B_L = 72, B_W = 80  ;
constexpr int RS_BYTES = 7 * 512 + 8 * 64;
constexpr int BAR_OQK = 1, BAR_S = 2, BAR_O = 3, BAR_ALL = 4, BAR_KVF = 5, BAR_AB = 6, BAR_AB2 = 7, BAR_C = 8;
constexpr int NTHREADS = 384;
constexpr int REG_C = CREG, REG_A = AREG;
static_assert(2 * REG_C + REG_A <= 504, "register pool");

#define PROF(slot) do {} while (0)
#define PROFN(slot) do {} while (0)
#define PROFS() do {} while (0)
#define PROF0(slot) do {} while (0)
#define PROF1(slot) do {} while (0)

struct Maps { CUtensorMap q, k, v, o; };

__device__ __forceinline__ void mmaq(float (&c)[4], const uint4& a, uint32_t b0, uint32_t b1) { mma16816(c, a.x, a.y, a.z, a.w, b0, b1); }
__device__ __forceinline__ int opaque(int v) { int d; asm volatile("mov.u32 %0, %1;" : "=r"(d) : "r"(v)); return d; }
__device__ __forceinline__ uint32_t dep(uint32_t base, uint32_t v, uint32_t zero) {
  uint32_t d; asm("lop3.b32 %0, %1, %2, %3, 0xF8;" : "=r"(d) : "r"(base), "r"(v), "r"(zero)); return d;
}
__device__ __forceinline__ uint32_t frag_off(int lane, int cp) {
  const int mat = lane >> 3, r = lane & 7;
  return ((mat >> 1) * 8 + r) * 128 + (((cp * 2 + (mat & 1)) ^ r) * 16);
}

template <bool EXTRA>
__device__ __forceinline__ void softmax_pv(int s, int x, uint32_t sb, uint32_t sl, uint32_t bar, int lane_in, int a, int head, uint32_t t0,
                                           uint32_t (&WX)[8][4], uint4& vm_out, int P) {
  const int lane = opaque(lane_in);
  uint4* const vm_ptr = g_Vmf + (size_t)head * NSEG * 128 + x * 32 + lane;
  const float sc = 0.08838834764831845f * 1.4426950408889634f;
  const uint32_t wa = sb + SM_WO + 4 * 16384 + frag_off(lane, x);
  bar_sync(BAR_S, 128);
  const uint4 s0 = lds128(sl + SM_S), s1 = lds128(sl + SM_S + 512), s2 = lds128(sl + SM_S + 1024);
  uint4 vx[4];
#pragma unroll
  for (int u = 0; u < 4; u++) vx[u] = lds128(sl + SM_VX + x * 2048 + u * 512);
  const bool okv = mbar_try(bar + B_XV, s & 1);
  const uint32_t lv = sb + x * 512 + lane * 8;
  float y[10] = {__uint_as_float(s0.x), __uint_as_float(s0.y), __uint_as_float(s0.z), __uint_as_float(s0.w),
                 __uint_as_float(s1.x), __uint_as_float(s1.y), __uint_as_float(s1.z), __uint_as_float(s1.w),
                 __uint_as_float(s2.x) + __uint_as_float(s2.z), __uint_as_float(s2.y) + __uint_as_float(s2.w)};
  float m = fmaxf(fmaxf(fmaxf(y[0], y[1]), fmaxf(y[2], y[3])), fmaxf(fmaxf(y[4], y[5]), fmaxf(y[6], y[7])));
  m = fmaxf(m, fmaxf(y[8], y[9]));
  if (P) PROF(12);
  m = fmaxf(m, __shfl_xor_sync(0xffffffffu, m, 1));
  m = fmaxf(m, __shfl_xor_sync(0xffffffffu, m, 2));
  if (!okv) mbar_wait(bar + B_XV, s & 1, t0);
  const uint2 ov0 = lds64(lv + SM_OV), xv0 = lds64(lv + SM_XV), ov1 = lds64(lv + SM_OV + 256), xv1 = lds64(lv + SM_XV + 256);
  if (EXTRA) {
#pragma unroll
    for (int u = 0; u < WXE; u++) ldsm4t(WX[u], wa + u * 2048);
  }
  const float mc = m * sc;
#pragma unroll
  for (int i = 0; i < 10; i++) y[i] = ex2(fmaf(y[i], sc, -mc));
  const uint32_t p0 = pack2(y[0], y[1]), p1 = pack2(y[2], y[3]), p2 = pack2(y[4], y[5]), p3 = pack2(y[6], y[7]), p4 = pack2(y[8], y[9]);
  const uint4 vm = make_uint4(hadd2bf(ov0.x, xv0.x), hadd2bf(ov0.y, xv0.y), hadd2bf(ov1.x, xv1.x), hadd2bf(ov1.y, xv1.y));
  float o0[4] = {0.f, 0.f, 0.f, 0.f}, o1[4] = {0.f, 0.f, 0.f, 0.f}, o2[4] = {0.f, 0.f, 0.f, 0.f}, o3[4] = {0.f, 0.f, 0.f, 0.f};
  mmaq(o0, vx[0], p0, p1); mmaq(o2, vx[2], p0, p1);
  mmaq(o0, vx[1], p2, p3); mmaq(o2, vx[3], p2, p3);
  mma1688(o1, vm.x, vm.y, p4); mma1688(o3, vm.z, vm.w, p4);
  asm volatile("stmatrix.sync.aligned.m8n8.x4.shared.b16 [%0], {%1,%2,%3,%4};" :: "r"(sl + SM_O + x * 512),
    "r"(pack2(o0[0] + o1[0], o0[1] + o1[1])), "r"(pack2(o0[2] + o1[2], o0[3] + o1[3])),
    "r"(pack2(o2[0] + o3[0], o2[1] + o3[1])), "r"(pack2(o2[2] + o3[2], o2[3] + o3[3])) : "memory");
  if (P) PROF(13);
  bar_arrive(BAR_O, NTHREADS);
  if (x != 3) bar_arrive(BAR_KVF, 128);
  if (EXTRA) {
#pragma unroll
    for (int u = WXE; u < 8; u++) ldsm4t(WX[u], wa + u * 2048);
    bar_sync(BAR_AB2, 128);
  } else {
    bar_arrive(BAR_AB2, 128);
    if (x == 3) {
      float l = ((y[0] + y[1]) + (y[2] + y[3])) + ((y[4] + y[5]) + (y[6] + y[7])) + (y[8] + y[9]);
      l += __shfl_xor_sync(0xffffffffu, l, 1);
      l += __shfl_xor_sync(0xffffffffu, l, 2);
      float inv; asm("rcp.approx.ftz.f32 %0, %1;" : "=f"(inv) : "f"(l));
      if ((lane & 3) == 0) sts32(sb + SM_INV + lane, __float_as_uint(inv));
      __syncwarp();
      mbar_arrive_if(bar + B_L, lane == 0 && s >= 0);
      bar_sync(BAR_KVF, 128);
    }
  }
  if (!EXTRA) { if (a == 0 && s >= 0) vm_ptr[(size_t)s * 128] = vm; } else vm_out = vm;
}

__device__ __forceinline__ void reduce_exchange(int x, int gi, int a, int s, uint32_t sb, uint32_t bar, int lane_in, uint32_t t0, int P, int bid) {
  const int lane = opaque(lane_in);
  const int tt = x * 32 + lane;
  const bool act = tt < 72;
  const int hc = lane & 1;
  const uint32_t rs_addr = sb + SM_RS + tt * 8;
  const uint32_t mem_addr = sb + SM_MEM + (x < 2 ? (tt >> 1) * 16 : 8 * 512 + (4 * gi + (lane >> 1)) * 16);
  const uint32_t mem_step = x < 2 ? 512 : 0;
  const uint32_t ma = mem_addr + (1 + hc) * mem_step;
  const uint32_t r0 = 2 * ((gi - 1 - hc) & 7) + a, r1 = 2 * ((gi - 3 - hc) & 7) + a, r2 = 2 * ((gi - 5 - hc) & 7) + a, r3 = 2 * ((gi - 7) & 7) + a;
  const uint32_t d0 = mapa(ma, r0), e0 = mapa(bar + B_AG + (x < 2 ? 8 : 32), r0);
  const uint32_t d1 = mapa(ma + 2 * mem_step, r1), e1_ = mapa(bar + B_AG + (x < 2 ? 16 : 32), r1);
  const uint32_t d2 = mapa(ma + 4 * mem_step, r2), e2_ = mapa(bar + B_AG + (x < 2 ? 24 : 32), r2);
  const uint32_t d3 = mapa(ma + 6 * mem_step, r3), e3_ = mapa(bar + B_AG + 32, r3);
  char* const xb = reinterpret_cast<char*>((reinterpret_cast<uintptr_t>(g_xch) + 8191) & ~(uintptr_t)8191) + (tt * 16 + (s & 1) * 2048);
  void* const xw = xb + (size_t)bid * 8192;
  const void* const xr1 = xb + (size_t)(bid ^ 16) * 8192;
  const void* const xr2 = xb + (size_t)(bid ^ 32) * 8192;
  const void* const xr3 = xb + (size_t)(bid ^ 48) * 8192;
  const uint32_t tag = (s + 1) & 15;
  mbar_wait(bar + B_RS, s & 1, t0);
  if (P) PROF(20);
  uint32_t w0 = 0, w1 = 0;
  if (act) {
    uint2 r[8];
#pragma unroll
    for (int u = 0; u < 8; u++) r[u] = lds64(rs_addr + u * 576);
    float f0 = ((bflo(r[0].x) + bflo(r[1].x)) + (bflo(r[2].x) + bflo(r[3].x))) + ((bflo(r[4].x) + bflo(r[5].x)) + (bflo(r[6].x) + bflo(r[7].x)));
    float f1 = ((bfhi(r[0].x) + bfhi(r[1].x)) + (bfhi(r[2].x) + bfhi(r[3].x))) + ((bfhi(r[4].x) + bfhi(r[5].x)) + (bfhi(r[6].x) + bfhi(r[7].x)));
    float f2 = ((bflo(r[0].y) + bflo(r[1].y)) + (bflo(r[2].y) + bflo(r[3].y))) + ((bflo(r[4].y) + bflo(r[5].y)) + (bflo(r[6].y) + bflo(r[7].y)));
    float f3 = ((bfhi(r[0].y) + bfhi(r[1].y)) + (bfhi(r[2].y) + bfhi(r[3].y))) + ((bfhi(r[4].y) + bfhi(r[5].y)) + (bfhi(r[6].y) + bfhi(r[7].y)));
    const uint32_t m0 = (__float_as_uint(f0) & ~15u) | tag;
    if (s >= 0) {
      st_b128(xw, m0, __float_as_uint(f1), __float_as_uint(f2), __float_as_uint(f3));
    }
    if (P) PROF(21);
    uint4 e1, e2, e3;
    const uint32_t mb = sb + SM_MB + tt * 16;
    uint32_t tn = clk32() + POLL_DELAY;
    while (true) {
      const uint32_t now = clk32();
      if ((int)(now - tn) >= 0) { cp_async16(mb, xr1); cp_async16(mb + 1152, xr2); cp_async16(mb + 2304, xr3); tn = now + POLL_GAP; }
      e1 = lds128(mb); e2 = lds128(mb + 1152); e3 = lds128(mb + 2304);
      if ((((e1.x ^ tag) | (e2.x ^ tag) | (e3.x ^ tag)) & 15u) == 0 || s < 0) break;
      if (now - t0 > TIMEOUT_CLKS) { g_err = 1; break; }
    }
    if (P) PROF(22);
    f0 = (__uint_as_float(m0) + __uint_as_float(e1.x)) + (__uint_as_float(e2.x) + __uint_as_float(e3.x));
    f1 = (f1 + __uint_as_float(e1.y)) + (__uint_as_float(e2.y) + __uint_as_float(e3.y));
    f2 = (f2 + __uint_as_float(e1.z)) + (__uint_as_float(e2.z) + __uint_as_float(e3.z));
    f3 = (f3 + __uint_as_float(e1.w)) + (__uint_as_float(e2.w) + __uint_as_float(e3.w));
    w0 = pack2(f0, f1); w1 = pack2(f2, f3);
    if (s >= 0) sts64(mem_addr + hc * 8, w0, w1);
  }
  __syncwarp();
  const uint32_t n0 = __shfl_xor_sync(0xffffffffu, w0, 1), n1 = __shfl_xor_sync(0xffffffffu, w1, 1);
  mbar_arrive_if(bar + B_AG + (x == 2 ? 32 : 0), lane == 0);
  if (act && s >= 0) {
    const uint32_t y0 = hc ? n0 : w0, y1 = hc ? n1 : w1, y2 = hc ? w0 : n0, y3 = hc ? w1 : n1;
    st_async16(d0, y0, y1, y2, y3, e0);
    st_async16(d1, y0, y1, y2, y3, e1_);
    st_async16(d2, y0, y1, y2, y3, e2_);
    if (!hc) st_async16(d3, y0, y1, y2, y3, e3_);
  }
  __syncwarp();
  if (P) PROF(23);
}

__global__ void __launch_bounds__(NTHREADS, 1)
chain_kernel(const __grid_constant__ Maps maps, const bf16* __restrict__ mem0, const bf16* x_in, const bf16* Wq, const bf16* Wk, const bf16* Wv,
             const bf16* Wo, uint32_t zero) {
  extern __shared__ __align__(1024) unsigned char smem_raw[];
  const uint32_t sb = smem_u32(smem_raw);
  const int tid = __shfl_sync(0xffffffffu, (int)threadIdx.x, threadIdx.x & 31);
  const int warp = __shfl_sync(0xffffffffu, tid >> 5, 0), lane = tid & 31;
  const int rank = blockIdx.x & 15;
  const int cl = blockIdx.x >> 4;
  const int bid = cl * 16 + rank;
  const int gi = rank >> 1, a = rank & 1, head = cl * 8 + gi;
  const uint32_t t0 = clk32();
  const uint32_t bar = sb + SM_BAR;
  const uint32_t sl = sb + lane * 16;
  TR_T(trs);
  auto krow = [&](int sp) { const int idx = sp >> 1; const int p = idx < 8 ? ((gi + idx) & 7) : 8; return 288 * a + 32 * p + 16 * (sp & 1); };
  if (tid == 32) atomicAdd(&g_resident, 1u);
  const int ln_r8 = ((bid & 3) * 4 + warp / 3) + (bid >> 2) * 16, ln_w = warp % 3;
  uint4 lnv[6];
  {
    const uint4* src = reinterpret_cast<const uint4*>(x_in + (size_t)(ln_r8 * 8 + (lane >> 2)) * DM) + ln_w * 24 + (lane & 3);
#pragma unroll
    for (int t = 0; t < 6; t++) lnv[t] = __ldg(src + t * 4);
  }
  if (tid >= 96) {
    const int i = tid - 96, idx = i >> 5, t = lane >> 2, j = lane & 3;
    const int p = idx < 8 ? ((gi + idx) & 7) : 8;
    const uint32_t* src = reinterpret_cast<const uint32_t*>(mem0 + t * DM + 288 * a + 32 * p + 2 * j);
    sts128(sb + SM_MEM + i * 16, src[0], src[4], src[8], src[12]);
    if (i < 216) sts128(sb + SM_MB + i * 16, 0, 0, 0, 0);
  }
  PROF0(39);
  if (tid >= 64 && tid < 68) asm volatile("prefetch.tensormap [%0];" :: "l"(&maps.q + (tid - 64)) : "memory");
  if (warp == 0) {
    if (lane == 0) {
      mbar_init(bar + B_AG, 2); mbar_init(bar + B_AG + 8, 1); mbar_init(bar + B_AG + 16, 1); mbar_init(bar + B_AG + 24, 1); mbar_init(bar + B_AG + 32, 2);
      mbar_init(bar + B_XQK, 1); mbar_init(bar + B_XV, 9); mbar_init(bar + B_RS, 2); mbar_init(bar + B_KV, 1); mbar_init(bar + B_L, 1);
      for (int i = 0; i < 5; i++) mbar_init(bar + B_W + i * 8, 1);
      asm volatile("fence.mbarrier_init.release.cluster;" ::: "memory");
      mbar_expect(bar + B_W, 20 * SLOT); mbar_expect(bar + B_W + 8, 16 * SLOT); mbar_expect(bar + B_W + 16, 9 * SLOT);
      mbar_expect(bar + B_W + 24, 5 * 16384); mbar_expect(bar + B_W + 32, 9 * SLOT);
    }
    __syncwarp();
  }
  {
    const int g = lane >> 2, j = lane & 3;
    const uint32_t red = sb + SM_S + (warp / 3) * 256;
    float f[48];
#pragma unroll
    for (int t = 0; t < 6; t++) {
      f[t * 8 + 0] = bflo(lnv[t].x); f[t * 8 + 1] = bfhi(lnv[t].x); f[t * 8 + 2] = bflo(lnv[t].y); f[t * 8 + 3] = bfhi(lnv[t].y);
      f[t * 8 + 4] = bflo(lnv[t].z); f[t * 8 + 5] = bfhi(lnv[t].z); f[t * 8 + 6] = bflo(lnv[t].w); f[t * 8 + 7] = bfhi(lnv[t].w);
    }
    float sum = 0.f;
#pragma unroll
    for (int i = 0; i < 48; i++) sum += f[i];
    sum += __shfl_xor_sync(~0u, sum, 1); sum += __shfl_xor_sync(~0u, sum, 2);
    if (j == 0) sts32(red + g * 16 + ln_w * 4, __float_as_uint(sum));
    PROF0(40);
    __syncthreads();
    uint4 r = lds128(red + g * 16);
    const float mean = (__uint_as_float(r.x) + __uint_as_float(r.y) + __uint_as_float(r.z)) * (1.f / DM);
    float q = 0.f;
#pragma unroll
    for (int i = 0; i < 48; i++) { f[i] -= mean; q = fmaf(f[i], f[i], q); }
    q += __shfl_xor_sync(~0u, q, 1); q += __shfl_xor_sync(~0u, q, 2);
    if (j == 0) sts32(red + 128 + g * 16 + ln_w * 4, __float_as_uint(q));
    __syncthreads();
    r = lds128(red + 128 + g * 16);
    const float rs = rsqrtf((__uint_as_float(r.x) + __uint_as_float(r.y) + __uint_as_float(r.z)) * (1.f / DM) + 1e-5f);
    uint4* dst = g_xnT + ((size_t)(ln_r8 >> 4) * 9 + ln_w * 3) * 1024 + (ln_r8 & 15) * 64 + j * 8 + g;
#pragma unroll
    for (int t = 0; t < 6; t++)
      stg128(dst + (t >> 1) * 1024 + (t & 1) * 32, pack2(f[t * 8] * rs, f[t * 8 + 1] * rs), pack2(f[t * 8 + 2] * rs, f[t * 8 + 3] * rs),
             pack2(f[t * 8 + 4] * rs, f[t * 8 + 5] * rs), pack2(f[t * 8 + 6] * rs, f[t * 8 + 7] * rs));
  }
  PROF0(41);
  __syncthreads();
  if (tid == 352) {
    asm volatile("red.release.gpu.global.add.u32 [%0], 1;" :: "l"(&g_cntX[bid < 4 ? 0 : 32]) : "memory");
  }
  __syncwarp();
  __syncwarp();
  PROF0(42);
  cluster_sync();
  PROF0(43);
  if (warp < 3) {
    if (lane == 0) {
      if (warp != 1) {
        const int m = warp >> 1;
        const CUtensorMap* mp = m ? &maps.q : &maps.k;
        for (int u = 0; u < 10; u++) tma3d(sb + SM_WO + (2 * u + 1 - m) * SLOT, mp, krow(NX + u), head * 2, bar + B_W);
        for (int u = 0; u < 8; u++) tma3d(sb + SM_X + (2 * u + 1 - m) * SLOT, mp, krow(u), head * 2, bar + B_W + 8);
      } else {
        for (int u = 0; u < 9; u++) tma3d(sb + SM_V2 + (4 + u) * SLOT, &maps.v, krow(NV2 + u), head * 2, bar + B_W + 16);
        for (int u = 0; u < 4; u++) tma3d(sb + SM_V2 + u * SLOT, &maps.v, krow(u), head * 2, bar + B_W + 32);
      }
    }
    __syncwarp();
  }

  if (warp < 8) {
    asm volatile("setmaxnreg.inc.sync.aligned.u32 %0;" :: "n"(REG_C));
    const int w = warp;
    const uint32_t wl = sb + (w >> 2) * 2048 + frag_off(lane, w & 3);
    const uint32_t wo = sb + SM_WO + (w >> 1) * 16384 + frag_off(lane, (w & 1) * 2);
    uint32_t Pqk[18 - NX][2][4], Pv[NPV][4];
    uint32_t Xqk[NX][2][4];
#pragma unroll
    for (int u = 0; u < 20; u++) for (int q = 0; q < 4; q++) Pqk[u >> 1][u & 1][q] = 0;
#pragma unroll
    for (int u = 0; u < NPV; u++) for (int q = 0; q < 4; q++) Pv[u][q] = 0;
#pragma unroll
    for (int u = 0; u < 2 * NX; u++) for (int q = 0; q < 4; q++) Xqk[u >> 1][u & 1][q] = 0;
    const uint32_t partner = rank ^ 1;
    const uint32_t pd = __shfl_sync(~0u, mapa(sb, partner) - sb, 0), od = __shfl_sync(~0u, mapa(sb, 2 * w + a) - sb, 0);
    const bool late = STAGGER && w >= 4;
    const uint32_t ag = bar + B_AG + (late ? 8 : 0);

    for (int s = -1; s < NSEG; s++) {
      const uint32_t par = s & 1;
      float q0[4] = {0.f, 0.f, 0.f, 0.f}, k0[4] = {0.f, 0.f, 0.f, 0.f}, q1[4] = {0.f, 0.f, 0.f, 0.f}, k1[4] = {0.f, 0.f, 0.f, 0.f};
      uint4 B[9] = {};
      uint32_t V2[NV2][4];
      auto qk = [&](int idx) {
        const int s0 = 2 * idx, s1 = 2 * idx + 1;
        if (s0 < NX) { mma16816(q0, Xqk[s0][0], B[idx].x, B[idx].y); mma16816(k0, Xqk[s0][1], B[idx].x, B[idx].y); }
        else { mma16816(q0, Pqk[s0 - NX][0], B[idx].x, B[idx].y); mma16816(k0, Pqk[s0 - NX][1], B[idx].x, B[idx].y); }
        if (s1 < NX) { mma16816(q1, Xqk[s1][0], B[idx].z, B[idx].w); mma16816(k1, Xqk[s1][1], B[idx].z, B[idx].w); }
        else { mma16816(q1, Pqk[s1 - NX][0], B[idx].z, B[idx].w); mma16816(k1, Pqk[s1 - NX][1], B[idx].z, B[idx].w); }
      };
      mbar_wait(bar + B_AG, par, t0);
      if (w == 0) { PROF(0); PROFN(24); PROFS(); }
      B[0] = lds128(sl + SM_MEM);
      qk(0);
      ldsm4t(V2[0], wl + SM_V2); ldsm4t(V2[1], wl + SM_V2 + SLOT);
      if (late) mbar_wait(bar + B_AG + 8, par, t0);
      mbar_wait(ag + 8, par, t0);
      if (w == 0) PROF(1);
      B[1] = lds128(sl + SM_MEM + 512); B[2] = lds128(sl + SM_MEM + 1024);
      bool ok = mbar_try(ag + 16, par);
      qk(1);
      if (!ok) mbar_wait(ag + 16, par, t0);
      B[3] = lds128(sl + SM_MEM + 1536); B[4] = lds128(sl + SM_MEM + 2048);
      ok = mbar_try(ag + 24, par);
      qk(2);
      ldsm4t(V2[2], wl + SM_V2 + 2 * SLOT); ldsm4t(V2[3], wl + SM_V2 + 3 * SLOT);
      qk(3);
      if (!ok) mbar_wait(ag + 24, par, t0);
      if (w == 0) PROF(2);
      B[5] = lds128(sl + SM_MEM + 2560); B[6] = lds128(sl + SM_MEM + 3072);
      ok = mbar_try(bar + B_AG + 32, par);
      qk(4);
      ldsm4t(V2[4], wl + SM_V2 + 4 * SLOT); ldsm4t(V2[5], wl + SM_V2 + 5 * SLOT);
      qk(5);
      if (!ok) mbar_wait(bar + B_AG + 32, par, t0);
      if (w == 0) PROF(3);
      B[7] = lds128(sl + SM_MEM + 3584); B[8] = lds128(sl + SM_MEM + 4096);
      qk(6);
      ldsm4t(V2[6], wl + SM_V2 + 6 * SLOT); ldsm4t(V2[7], wl + SM_V2 + 7 * SLOT);
      qk(7);
      if (late) bar_arrive(BAR_AB, 256);
      qk(8);
      const uint32_t pq0 = pack2(q0[0] + q1[0], q0[1] + q1[1]);
      {
        const uint32_t c0 = movmat(pq0), c1 = movmat(pack2(q0[2] + q1[2], q0[3] + q1[3]));
        const uint32_t c2 = movmat(pack2(k0[0] + k1[0], k0[1] + k1[1])), c3 = movmat(pack2(k0[2] + k1[2], k0[3] + k1[3]));
        const bool swp = sl & 128;
        const uint32_t y0 = swp ? c2 : c0, y1 = swp ? c3 : c1, y2 = swp ? c0 : c2, y3 = swp ? c1 : c3;
        if (s >= 0) st_async16(sl + (pd + w * 512 + SM_XQK), y0, y1, y2, y3, bar + pd + B_XQK);
        sts128(sl + (w * 512 + SM_OQK), y0, y1, y2, y3);
        bar_arrive(BAR_OQK, NTHREADS);
      }
      if (w == 0) PROF(4);
      if (w == 4) PROF(14);
      ldsm4t(V2[8], wl + SM_V2 + 8 * SLOT);
      if (STAGGER && !late) bar_sync(BAR_AB, 256);
      const float vz = __uint_as_float(pq0 & zero);
      float v[4][4] = {{vz, 0.f, 0.f, 0.f}, {vz, 0.f, 0.f, 0.f}, {vz, 0.f, 0.f, 0.f}, {vz, 0.f, 0.f, 0.f}};
      uint32_t WO[16][4];
      if (s == 0) mbar_wait(bar + B_W + 24, 0, t0);
#pragma unroll
      for (int idx = 0; idx < 9; idx++) {
        const int s0 = 2 * idx, s1 = 2 * idx + 1;
        if (s0 < NV2) mma16816(v[s0 & 3], V2[s0], B[idx].x, B[idx].y); else mma16816(v[s0 & 3], Pv[s0 - NV2], B[idx].x, B[idx].y);
        if (s1 < NV2) mma16816(v[s1 & 3], V2[s1], B[idx].z, B[idx].w); else mma16816(v[s1 & 3], Pv[s1 - NV2], B[idx].z, B[idx].w);
        if (idx >= 9 - WEARLY) ldsm4t(WO[idx - (9 - WEARLY)], wo + (idx - (9 - WEARLY)) * 2048);
      }
      {
        const uint32_t vo0 = pack2((v[0][0] + v[1][0]) + (v[2][0] + v[3][0]), (v[0][1] + v[1][1]) + (v[2][1] + v[3][1]));
        const uint32_t vo1 = pack2((v[0][2] + v[1][2]) + (v[2][2] + v[3][2]), (v[0][3] + v[1][3]) + (v[2][3] + v[3][3]));
        const uint32_t l8 = (sl - sb) >> 1;
        if (s >= 0) st_async8(l8 + (sb + pd + w * 256 + SM_XV), vo0, vo1, bar + pd + B_XV);
        sts64(l8 + (sb + w * 256 + SM_OV), vo0, vo1);
        __syncwarp();
        mbar_arrive_if(bar + B_XV, sl == sb && s >= 0);
      }
      if (w == 0) PROF(5);
      if (s == NSEG - 1) break;
#pragma unroll
      for (int u = WEARLY; u < 16; u++) ldsm4t(WO[u], dep(u >= 8 ? wo ^ 32 : wo, WO[(u < 16 - WLATE ? u : 16 - WLATE) - 1][0], zero) + (u & 7) * 2048);
      if (w == 0) PROF(6);
      bar_sync(BAR_O, NTHREADS);
      {
        float m0[4] = {0.f, 0.f, 0.f, 0.f}, m1[4] = {0.f, 0.f, 0.f, 0.f}, m2[4] = {0.f, 0.f, 0.f, 0.f}, m3[4] = {0.f, 0.f, 0.f, 0.f};
        uint32_t ob[4][4];
        bool okl = false;
#pragma unroll
        for (int u = 0; u < 4; u++) ldsm4t(ob[u], sl + SM_O + u * 512);
#pragma unroll
        for (int u = 0; u < 3; u++) {
          mma16816(m0, WO[2 * u], ob[u][0], ob[u][1]);     mma16816(m1, WO[8 + 2 * u], ob[u][0], ob[u][1]);
          mma16816(m2, WO[2 * u + 1], ob[u][2], ob[u][3]); mma16816(m3, WO[8 + 2 * u + 1], ob[u][2], ob[u][3]);
          if (u == 1) okl = mbar_try(bar + B_L, par);
        }
        mma16816(m0, WO[6], ob[3][0], ob[3][1]); mma16816(m1, WO[14], ob[3][0], ob[3][1]);
        if (!okl) mbar_wait(bar + B_L, par, t0);
        const uint2 iv = lds64(sb + SM_INV + ((sl >> 1) & 24));
        mma16816(m2, WO[7], ob[3][2], ob[3][3]); mma16816(m3, WO[15], ob[3][2], ob[3][3]);
        const float i0 = __uint_as_float(iv.x), i1 = __uint_as_float(iv.y);
        const uint32_t c0 = movmat(pack2((m0[0] + m2[0]) * i0, (m0[1] + m2[1]) * i1)), c1 = movmat(pack2((m0[2] + m2[2]) * i0, (m0[3] + m2[3]) * i1));
        const uint32_t c2 = movmat(pack2((m1[0] + m3[0]) * i0, (m1[1] + m3[1]) * i1)), c3 = movmat(pack2((m1[2] + m3[2]) * i0, (m1[3] + m3[3]) * i1));
        if (w == gi) {
          sts128(sl + SM_RS + gi * 576, c0, c1, c2, c3);
          __syncwarp();
          mbar_arrive_if(bar + B_RS, sl == sb && s >= 0);
        } else {
          if (s >= 0) st_async16(sl + (od + SM_RS + gi * 576), c0, c1, c2, c3, bar + od + B_RS);
        }
      }
      if (w == 0) PROF(10);
      if (w == 4) PROF(15);
      if (s < 0) {
        if (w == 3) PROF1(44);
        mbar_wait(bar + B_W, 0, t0);
#pragma unroll
        for (int u = 0; u < 20; u++) ldsm4t(Pqk[u >> 1][u & 1], wl + SM_WO + u * SLOT);
        mbar_wait(bar + B_W + 16, 0, t0);
#pragma unroll
        for (int u = 0; u < NPV; u++) ldsm4t(Pv[u], wl + SM_V2 + (4 + u) * SLOT);
        if (w == 3) PROF1(45);
        bar_sync(BAR_C, 256);
        if (w == 0) {
          if (lane < 5) tma3d(sb + SM_V2 + (4 + lane) * SLOT, &maps.v, krow(4 + lane), head * 2, bar + B_W + 32);
          else if (lane < 10) tma2d(sb + SM_WO + (lane - 5) * 16384, &maps.o, 288 * a + 64 * (lane - 5), head * DH, bar + B_W + 24);
          __syncwarp();
        }
        bar_arrive(BAR_ALL, NTHREADS);
        mbar_wait(bar + B_W + 8, 0, t0);
        mbar_wait(bar + B_W + 32, 0, t0);
      }
      uint32_t keep = 0;
#pragma unroll
      for (int u = 0; u < 2 * NX; u++) {
        if (u == 6) mbar_wait(bar + B_RS, par, t0);
        if (u == 7 || u == 15) { float dz[4] = {0.f, 0.f, 0.f, 0.f}; mma16816(dz, Xqk[(u - 1) >> 1][(u - 1) & 1], zero, zero); keep = __float_as_uint(dz[0]); }
        ldsm4t(Xqk[u >> 1][u & 1], (u < 1 ? wl : dep(wl, (u == 7 || u == 15) && KEEPALIVE ? keep : Xqk[(u - 1) >> 1][(u - 1) & 1][0], zero)) + SM_X + u * SLOT);
      }
      if (w == 0) PROF(11);
    }
    __syncwarp();
    cluster_sync();
  } else {
    asm volatile("setmaxnreg.dec.sync.aligned.u32 %0;" :: "n"(REG_A));
    const int x = warp - 8;
    const int g = lane >> 2, j = lane & 3;
    const uint32_t sa = sb + SM_S + x * 512 + (32 * j + 4 * (g >> 1) + (g & 1)) * 4;
    const uint32_t sq = sl + (lane & 8);
    if (x < 2) {
      bar_arrive(BAR_ALL, NTHREADS);
      for (int s = -1; s < NSEG - 1; s++) {
        const uint32_t par = s & 1;
        uint4 R[8];
        if (s == 0) mbar_wait(bar + B_W + 24, 0, t0);
        mbar_wait(bar + B_KV, par, t0);
#pragma unroll
        for (int u = 0; u < 8; u++) R[u] = lds128(sl + SM_KX + x * 4096 + u * 512);
        float c0[4] = {0.f, 0.f, 0.f, 0.f}, c1[4] = {0.f, 0.f, 0.f, 0.f}, c2[4] = {0.f, 0.f, 0.f, 0.f}, c3[4] = {0.f, 0.f, 0.f, 0.f};
        bar_sync(BAR_OQK, NTHREADS);
        uint2 o[8];
#pragma unroll
        for (int u = 0; u < 8; u++) o[u] = lds64(sq + SM_OQK + u * 512);
        if (x == 0) PROF(16);
        mbar_wait(bar + B_XQK, par, t0);
        if (x == 0) PROF(17);
        {
          uint2 b[8];
#pragma unroll
          for (int u = 0; u < 8; u++) b[u] = lds64(sq + SM_XQK + u * 512);
#pragma unroll
          for (int u = 0; u < 8; u++) { b[u].x = hadd2bf(b[u].x, o[u].x); b[u].y = hadd2bf(b[u].y, o[u].y); }
          mmaq(c0, R[0], b[0].x, b[0].y); mmaq(c1, R[1], b[1].x, b[1].y); mmaq(c2, R[2], b[2].x, b[2].y); mmaq(c3, R[3], b[3].x, b[3].y);
          mmaq(c0, R[4], b[4].x, b[4].y); mmaq(c1, R[5], b[5].x, b[5].y); mmaq(c2, R[6], b[6].x, b[6].y); mmaq(c3, R[7], b[7].x, b[7].y);
        }
        sts32(sa, __float_as_uint((c0[0] + c1[0]) + (c2[0] + c3[0])));
        sts32(sa + 64, __float_as_uint((c0[1] + c1[1]) + (c2[1] + c3[1])));
        sts32(sa + 8, __float_as_uint((c0[2] + c1[2]) + (c2[2] + c3[2])));
        sts32(sa + 72, __float_as_uint((c0[3] + c1[3]) + (c2[3] + c3[3])));
        if (x == 0) PROF(18);
        uint32_t WX[8][4];
        uint4 vmo;
        softmax_pv<true>(s, x, sb, sl, bar, lane, a, head, t0, WX, vmo, x == 0);
        {
          float m0[4] = {0.f, 0.f, 0.f, 0.f}, m1[4] = {0.f, 0.f, 0.f, 0.f}, m2[4] = {0.f, 0.f, 0.f, 0.f}, m3[4] = {0.f, 0.f, 0.f, 0.f};
          uint32_t ob[4][4];
#pragma unroll
          for (int u = 0; u < 4; u++) ldsm4t(ob[u], sl + SM_O + u * 512);
          const int ln = opaque(lane);
          const uint32_t r_rs2 = mapa(sb + SM_RS + gi * 576 + (32 + (ln & 3)) * 16 + x * 8, 2 * (ln >> 2) + a), r_rsb2 = mapa(bar + B_RS, 2 * (ln >> 2) + a);
          mma16816(m0, WX[0], ob[0][0], ob[0][1]); mma16816(m1, WX[1], ob[0][2], ob[0][3]);
          mma16816(m2, WX[2], ob[1][0], ob[1][1]); mma16816(m3, WX[3], ob[1][2], ob[1][3]);
          mma16816(m0, WX[4], ob[2][0], ob[2][1]); mma16816(m1, WX[5], ob[2][2], ob[2][3]);
          mma16816(m2, WX[6], ob[3][0], ob[3][1]); mma16816(m3, WX[7], ob[3][2], ob[3][3]);
          mbar_wait(bar + B_L, par, t0);
          const uint2 iv = lds64(sb + SM_INV + (ln & 3) * 8);
          const float i0 = __uint_as_float(iv.x), i1 = __uint_as_float(iv.y);
          const uint32_t d0 = movmat(pack2(((m0[0] + m1[0]) + (m2[0] + m3[0])) * i0, ((m0[1] + m1[1]) + (m2[1] + m3[1])) * i1));
          const uint32_t d1 = movmat(pack2(((m0[2] + m1[2]) + (m2[2] + m3[2])) * i0, ((m0[3] + m1[3]) + (m2[3] + m3[3])) * i1));
          if (s >= 0) st_async8(r_rs2, d0, d1, r_rsb2);
          if (a == 0 && s >= 0) g_Vmf[((size_t)head * NSEG + s) * 128 + x * 32 + ln] = vmo;
        }
        if (x == 0) PROF(19);
        reduce_exchange(x, gi, a, s, sb, bar, lane, t0, x == 0, bid);
      }
      bar_sync(BAR_OQK, NTHREADS);
    } else {
      const unsigned epoch = g_epoch + 1;
      const uint4* kx_g = g_Kf + (size_t)head * 128 * 256;
      const uint4* vx_g = g_Vf + (size_t)head * NSEG * 512;
      const int hh = x - 2;
      const uint32_t sm_ = sa - hh * 512 + hh * 8;
      uint4* const km_ptr = g_Kmf + (size_t)head * NSEG * 128 + hh * 64 + lane;
      if (x == 2) bar_arrive(BAR_ALL, NTHREADS);
      for (int s = -1; s < NSEG; s++) {
        const uint32_t par = s & 1;
        uint2 Q[4], K[4], oq[4], okk[4];
        if (s < NSEG - 1) mbar_wait(bar + B_KV, par, t0);
        bar_sync(BAR_OQK, NTHREADS);
#pragma unroll
        for (int u = 0; u < 4; u++) { Q[u] = lds64(sq + SM_OQK + (hh * 4 + u) * 512); K[u] = lds64((sq ^ 8) + SM_OQK + (hh * 4 + u) * 512); }
        mbar_wait(bar + B_XQK, par, t0);
        float c0[4] = {0.f, 0.f, 0.f, 0.f}, c1[4] = {0.f, 0.f, 0.f, 0.f}, c2[4] = {0.f, 0.f, 0.f, 0.f}, c3[4] = {0.f, 0.f, 0.f, 0.f};
#pragma unroll
        for (int u = 0; u < 4; u++) { oq[u] = lds64(sq + SM_XQK + (hh * 4 + u) * 512); okk[u] = lds64((sq ^ 8) + SM_XQK + (hh * 4 + u) * 512); }
#pragma unroll
        for (int u = 0; u < 4; u++) {
          Q[u].x = hadd2bf(Q[u].x, oq[u].x); Q[u].y = hadd2bf(Q[u].y, oq[u].y); K[u].x = hadd2bf(K[u].x, okk[u].x); K[u].y = hadd2bf(K[u].y, okk[u].y);
        }
#pragma unroll
        for (int u = 0; u < 4; u += 2) {
          mma1688(c0, K[u].x, K[u].y, Q[u].x);
          mma1688(c1, K[u].x, K[u].y, Q[u].y);
          mma1688(c2, K[u + 1].x, K[u + 1].y, Q[u + 1].x);
          mma1688(c3, K[u + 1].x, K[u + 1].y, Q[u + 1].y);
        }
        sts32(sm_, __float_as_uint((c0[0] + c1[2]) + (c2[0] + c3[2])));
        sts32(sm_ + 64, __float_as_uint((c0[1] + c1[3]) + (c2[1] + c3[3])));
        uint32_t dummy[8][4]; uint4 dummy4;
        if (s < NSEG - 1) softmax_pv<false>(s, x, sb, sl, bar, lane, a, head, t0, dummy, dummy4, 0);
        if (a == 0 && s >= 0) {
          km_ptr[(size_t)s * 128] = make_uint4(K[0].x, K[0].y, K[1].x, K[1].y);
          km_ptr[(size_t)s * 128 + 32] = make_uint4(K[2].x, K[2].y, K[3].x, K[3].y);
        }
        if (s == NSEG - 1) break;
        if (x == 2) {
          reduce_exchange(x, gi, a, s, sb, bar, lane, t0, 0, bid);
          if (lane == 0) mbar_expect(bar + B_RS, RS_BYTES);
        } else {
          if (lane == 0 && s >= 0 && s + 1 < NSEG - 1) {
            mbar_expect(bar + B_KV, 16384);
            bulk_g2s(sb + SM_KX, kx_g + (size_t)(s + 1) * 512, 8192, bar + B_KV);
            bulk_g2s(sb + SM_VX, vx_g + (size_t)(s + 1) * 512, 8192, bar + B_KV);
          }
          __syncwarp();
          mbar_wait(bar + B_RS, par, t0);
          if (lane == 0) {
            const int nb = s < 0 ? 0 : 1024;
            mbar_expect(bar + B_AG + 8, nb); mbar_expect(bar + B_AG + 16, nb); mbar_expect(bar + B_AG + 24, nb); mbar_expect(bar + B_AG + 32, s < 0 ? 0 : 960);
            mbar_expect(bar + B_XQK, 4096); mbar_expect(bar + B_XV, 2048);
            if (a == 0 && (s & 3) == 0 && s > 0) { st_release(&g_memflag[head * 8], epoch * 64 + s); if (bid == 0) TR_LOG(9 | (((s - 1) >> 2) << 24), trs, trs); }
            if ((s & 3) == 2 && s + 2 < NSEG) {
              while (ld_acquire(&g_kvflag[((s + 2) >> 2) * 64 + head]) != epoch) { if (timed_out(t0)) break; }
              while (ld_acquire(&g_kvflag[((s + 2) >> 2) * 64 + 32 + head]) != epoch) { if (timed_out(t0)) break; }
              asm volatile("fence.proxy.async.global;" ::: "memory");
              asm volatile("cp.async.bulk.prefetch.L2.global [%0], 32768;" :: "l"(kx_g + (size_t)(s + 2) * 512) : "memory");
              asm volatile("cp.async.bulk.prefetch.L2.global [%0], 32768;" :: "l"(vx_g + (size_t)(s + 2) * 512) : "memory");
            }
          }
          __syncwarp();
          if (s >= 0) {
            float dz[4] = {0.f, 0.f, 0.f, 0.f};
            while (true) {
              mma16816(dz, zero, zero, zero, zero, zero, zero);
              if (__all_sync(~0u, mbar_test(bar + B_AG + __float_as_uint(dz[0]), par ^ 1) || timed_out(t0))) break;
              __nanosleep(KEEPALIVE);
            }
          }
          if (s < 0) {
            __syncwarp();
            bar_sync(BAR_ALL, NTHREADS);
            if (lane == 0) {
              while (ld_acquire(&g_kvflag[head]) != epoch) { if (timed_out(t0)) break; __nanosleep(100); }
              while (ld_acquire(&g_kvflag[32 + head]) != epoch) { if (timed_out(t0)) break; __nanosleep(100); }
              asm volatile("fence.proxy.async.global;" ::: "memory");
              mbar_expect(bar + B_KV, 16384);
              bulk_g2s(sb + SM_KX, kx_g, 8192, bar + B_KV);
              bulk_g2s(sb + SM_VX, vx_g, 8192, bar + B_KV);
            }
          }
        }
        __syncwarp();
      }
    }
    {
      mbar_wait(bar + B_XV, (NSEG - 1) & 1, t0);
      const uint32_t lv = sb + x * 512 + lane * 8;
      const uint2 ov0 = lds64(lv + SM_OV), xv0 = lds64(lv + SM_XV), ov1 = lds64(lv + SM_OV + 256), xv1 = lds64(lv + SM_XV + 256);
      if (a == 0) g_Vmf[((size_t)head * NSEG + NSEG - 1) * 128 + x * 32 + lane] = make_uint4(hadd2bf(ov0.x, xv0.x), hadd2bf(ov0.y, xv0.y), hadd2bf(ov1.x, xv1.x), hadd2bf(ov1.y, xv1.y));
      bar_sync(BAR_S, 128);
      if (x == 3 && a == 0 && lane == 0) { st_release(&g_memflag[head * 8], (g_epoch + 1) * 64 + 64); if (bid == 0) TR_LOG(9 | (15 << 24), trs, trs); }
    }
    __syncwarp();
    cluster_sync();
  }
}
}
__device__ __align__(1024) uint4 g_hnT[NRB * 9 * 1024];
__device__ __align__(1024) uint4 g_oT[NRB * 64 * 1024];
__device__ __align__(1024) uint4 g_gT[NRB * 72 * 1024];
constexpr int MAXSPLIT = 6;
__device__ __align__(1024) uint4 g_p1[MAXSPLIT * 256 * 18 * 32];
__device__ __align__(1024) uint4 g_p2[MAXSPLIT * 256 * 18 * 32];
__device__ __align__(1024) uint4 g_hT[256 * 18 * 32];

__global__ void gate_kernel() {
  const uint32_t t0 = clk32();
  const unsigned need = (g_epoch + 1) * 64u;
  while ((int)(ld_relaxed(&g_resident) - need) < 0) { if (timed_out(t0)) break; }
}
namespace mega {
constexpr int NS = 5;
constexpr int SM_B = 0, SM_A = 9 * 16384, SM_BAR = SM_A + NS * 16384;
constexpr int B_FA = 0, B_EA = NS * 8, B_FB = 2 * NS * 8, B_EB = B_FB + 96, B_D = B_EB + 24, B_TK = B_D + 32, B_QF = B_TK + 32, B_QE = B_QF + 16,
              B_PD = B_QE + 16, B_PE = B_PD + 16, B_BF = B_PE + 16, B_BE = B_BF + 8;
constexpr int SM_DESC = SM_BAR + 512;
constexpr int SM_TQ = SM_DESC + 64;
constexpr int SM_TK = SM_TQ + 32;
constexpr int SM_PUB = SM_TK + 16;
constexpr int SM_RED = SM_PUB + 16;
constexpr int SM_TOTAL = SM_RED + 256;
enum { T_K = 0, T_V = 1, T_QA = 2, T_OP = 3, T_F1 = 4, T_F2 = 5, T_END = 6 };
constexpr int NORDER = 468;
__constant__ unsigned short c_order[NORDER] = {
  1408,3456,5504,7552,9600,11648,13696,15744,17792,19840,21888,23936,25984,28032,30080,32128,34176,36224,38272,40320,
  42368,44416,46464,48512,50560,52608,54656,56704,58752,60800,62848,64896,514,2562,4610,6658,8706,10754,12802,14850,
  728,2776,4824,6872,8920,10968,13016,15064,17112,19160,21208,23256,25304,27352,29400,31448,16898,18946,20994,23042,
  25090,27138,29186,31234,546,2594,4642,6690,8738,10786,12834,14882,515,2563,4611,6659,8707,10755,12803,14851,
  16899,18947,20995,23043,25091,27139,29187,31235,33283,35331,33496,35544,37592,39640,41688,43736,45784,47832,49880,51928,
  53976,56024,58072,60120,62168,64216,516,2564,4612,6660,8708,10756,12804,14852,16900,16930,18978,21026,23074,25122,
  27170,29218,31266,547,2595,4643,6691,8739,10787,12835,14883,16931,18948,20996,23044,25092,27140,29188,31236,33284,
  35332,18979,21027,23075,25123,27171,29219,31267,33315,35363,450,2498,4546,6594,8642,10690,12738,14786,517,2565,
  4613,6661,8709,10757,12805,14853,16901,18949,20997,23045,25093,27141,29189,31237,33285,35333,16834,18882,20930,22978,
  25026,27074,29122,31170,548,2596,4644,6692,8740,10788,12836,14884,16932,18980,21028,23076,25124,27172,29220,31268,
  33316,35364,451,2499,4547,6595,8643,10691,12739,14787,16835,18883,20931,22979,25027,27075,29123,31171,33219,35267,
  549,2597,4645,6693,8741,10789,12837,14885,16933,18981,21029,23077,25125,27173,29221,31269,33317,35365,474,2522,
  4570,6618,8666,10714,12762,14810,16858,18906,20954,23002,25050,27098,29146,31194,452,2500,4548,6596,8644,10692,
  12740,14788,16836,475,2523,4571,6619,8667,10715,12763,14811,16859,18907,20955,23003,25051,27099,29147,31195,33243,
  35291,370,2418,4466,6514,8562,10610,12658,14706,16754,18802,20850,22898,24946,26994,29042,31090,243,2291,4339,
  6387,8435,10483,12531,14579,16627,18884,20932,22980,25028,27076,29124,31172,33220,35268,453,2501,4549,6597,8645,
  10693,12741,14789,16837,18675,20723,22771,24819,26867,28915,30963,33011,35059,476,2524,4572,6620,8668,10716,12764,
  14812,16860,251,2299,4347,6395,8443,10491,12539,14587,16635,18885,20933,22981,25029,27077,29125,31173,33221,35269,
  18683,20731,22779,24827,26875,28923,30971,33019,35067,18908,20956,23004,25052,27100,29148,31196,33244,35292,477,2525,
  4573,6621,8669,10717,12765,14813,16861,18909,20957,23005,25053,27101,29149,31197,33245,35293,244,2292,4340,6388,
  8436,10484,12532,14580,16628,18676,20724,22772,24820,26868,28916,30964,33012,35060,252,2300,4348,6396,8444,10492,
  12540,14588,16636,245,2293,4341,6389,8437,10485,12533,14581,16629,18684,20732,22780,24828,26876,28924,30972,33020,
  35068,18677,20725,22773,24821,26869,28917,30965,33013,35061,253,2301,4349,6397,8445,10493,12541,14589,16637,18685,
  20733,22781,24829,26877,28925,30973,33021,35069,
};
constexpr int NTASK = NORDER;
constexpr int NWTASK = 2048;
constexpr int SPL = 6;
#define F1SPLIT 1
#define PFA 0
#define PFB 0
#define LATECLAIM 260
#define LATETH 1
#define PRE 2
constexpr int REG_C = 192, REG_P = 120;
static_assert(2 * REG_C + REG_P <= 504, "register pool");

__device__ unsigned g_ticket, g_wticket;
constexpr int PAD = 32;
__device__ unsigned g_cntO[NRB * 8 * PAD], g_cntP1[NRB * PAD], g_cntH[NRB * PAD], g_cntG[NRB * 8 * PAD], g_cntP2[NRB * PAD], g_done;

template <int B> struct IntC { static constexpr int value = B; };
__device__ __forceinline__ void red_release(unsigned* p) { asm volatile("red.release.gpu.global.add.u32 [%0], 1;" :: "l"(p) : "memory"); }
__device__ __forceinline__ void wait_cnt(const unsigned* p, unsigned need, int far, uint32_t t0) {
  while (true) {
    const int d = (int)(ld_relaxed(p) - need);
    if (d >= 0) break;
    if (timed_out(t0)) break;
    __nanosleep(d <= -far ? 1000 : 40);
  }
  (void)ld_acquire(p);
}
__device__ __forceinline__ float gelu_tanh(float z) {
  const float u = z * fmaf(z * z, 0.044715f * 0.7978845608028654f, 0.7978845608028654f);
  float t; asm("tanh.approx.f32 %0, %1;" : "=f"(t) : "f"(u));
  const float hz = 0.5f * z;
  return fmaf(hz, t, hz);
}
__device__ __forceinline__ void acc8(float (&f)[8], const uint4& v) {
  f[0] += bflo(v.x); f[1] += bfhi(v.x); f[2] += bflo(v.y); f[3] += bfhi(v.y);
  f[4] += bflo(v.z); f[5] += bfhi(v.z); f[6] += bflo(v.w); f[7] += bfhi(v.w);
}

__device__ __forceinline__ void arrive2_if(uint32_t local, uint32_t pd, int p, int cnt) {
  asm volatile("{ .reg .pred q; setp.ne.b32 q, %2, 0; @q mbarrier.arrive.shared::cta.b64 _, [%0], %3; @q mbarrier.arrive.shared::cluster.b64 _, [%1], %3; }"
    :: "r"(local), "r"(local + pd), "r"(p), "r"(cnt) : "memory");
}
__device__ __forceinline__ void bulk_mc(uint32_t dst, const void* src, uint32_t bytes, uint32_t bar) {
  asm volatile("cp.async.bulk.shared::cluster.global.mbarrier::complete_tx::bytes.multicast::cluster [%0], [%1], %2, [%3], %4;"
    :: "r"(dst), "l"(src), "r"(bytes), "r"(bar), "h"((uint16_t)3) : "memory");
}
__device__ __forceinline__ int op_kb0(int kc) { return kc < 2 ? 12 * kc : 4 + 10 * kc; }
__device__ __forceinline__ int task_nkb(int type, int kc) { return type == T_OP ? (kc < 2 ? 12 : 10) : type == T_F2 ? 12 : 9; }

__device__ __forceinline__ void finish(unsigned epoch) {
  if (atomicAdd(&g_done, 1u) == epoch * 3 * gridDim.x - 1) { g_ticket = 0; g_wticket = 0; g_epoch = epoch; }
}
struct Maps { CUtensorMap m[6]; };
struct WPtr { const char* p[6]; };

__global__ void __launch_bounds__(384, 1)
mega_kernel(const __grid_constant__ Maps maps, const bf16* __restrict__ x, const bf16* __restrict__ b1, const bf16* __restrict__ b2,
            bf16* __restrict__ out, const __grid_constant__ WPtr wp) {
  extern __shared__ __align__(1024) unsigned char smem_raw[];
  const uint32_t sb = smem_u32(smem_raw);
  const int tid = threadIdx.x, wg = __shfl_sync(~0u, tid >> 7, 0), lane = tid & 31, w = __shfl_sync(~0u, (tid >> 5) & 3, 0);
  const uint32_t bar = sb + SM_BAR;
  const uint32_t t0 = clk32();
  if (tid == 0) {
    for (int i = 0; i < NS; i++) { mbar_init(bar + B_FA + i * 8, 1); mbar_init(bar + B_EA + i * 8, 8); }
    for (int i = 0; i < 3; i++) mbar_init(bar + B_FB + i * 8, 1);
    for (int i = 0; i < 3; i++) mbar_init(bar + B_EB + i * 8, 4);
    for (int i = 0; i < 4; i++) mbar_init(bar + B_D + i * 8, 1);
    for (int i = 0; i < 4; i++) mbar_init(bar + B_TK + i * 8, 1);
    for (int i = 0; i < 2; i++) { mbar_init(bar + B_QF + i * 8, 1); mbar_init(bar + B_QE + i * 8, 1); mbar_init(bar + B_PD + i * 8, 4); mbar_init(bar + B_PE + i * 8, 1); }
    mbar_init(bar + B_BF, 1); mbar_init(bar + B_BE, 1);
    asm volatile("fence.mbarrier_init.release.cluster;" ::: "memory");
  }
  const int rank = blockIdx.x & 1;
  const uint32_t pd = __shfl_sync(~0u, mapa(sb, rank ^ 1) - sb, 0);
  const unsigned ep0 = *(volatile unsigned*)&g_epoch;
  const unsigned epoch = ep0 + 1;
  __syncthreads();
  asm volatile("barrier.cluster.arrive.relaxed.aligned; barrier.cluster.wait.aligned;" ::: "memory");
  if (wg == 2) {
    asm volatile("setmaxnreg.dec.sync.aligned.u32 %0;" :: "n"(REG_P));
    if (w == 0) {
      {
        int st = 0, ph = 1, seq = 0, qi = 0;
        uint32_t bjob = 0, ebph = 1; int th = 3, bj = 0;
        auto bservice = [&]() {
          if (th == 3) {
            if (!mbar_test(bar + B_BF, bj & 1)) return;
            asm volatile("ld.shared.b32 %0, [%1];" : "=r"(bjob) : "r"(sb + SM_RED) : "memory");
            bjob = __shfl_sync(~0u, bjob, 0);
            th = 0; bj++;
          }
          if (!mbar_test(bar + B_EB + th * 8, ebph)) return;
          const int type = bjob & 255, sl = (bjob >> 8) & 255, kc = (bjob >> 16) & 255;
          const CUtensorMap* mp = &maps.m[type];
          const uint32_t fb = bar + B_FB + th * 8, dst = sb + SM_B + th * 49152;
          if (elect()) {
            mbar_expect(fb, 49152);
            if (type <= T_QA) tma3d(dst, mp, th * 192, sl * 2, fb);
            else if (type == T_F1) { tma5d(dst, mp, sl * 128, th * 6, fb); tma5d(dst + 24576, mp, sl * 128 + 64, th * 6, fb); }
            else {
              const int u0 = (type == T_OP ? op_kb0(kc) : kc * 12) * 2 + th * 8;
              tma5d(dst, mp, sl * 96, u0, fb); tma5d(dst + 16384, mp, sl * 96 + 32, u0, fb); tma5d(dst + 32768, mp, sl * 96 + 64, u0, fb);
            }
            if (th == 2) mbar_arrive(bar + B_BE);
          }
          if (++th == 3) ebph ^= 1;
        };
        auto pwait = [&](uint32_t b, uint32_t par) {
          while (!mbar_test(b, par)) { bservice(); if (timed_out(t0)) break; }
        };
        auto pop = [&]() {
          pwait(bar + B_QF + (qi & 1) * 8, (qi >> 1) & 1);
          uint2 e = lds64(sb + SM_TQ + (qi & 1) * 16);
          e.x = __shfl_sync(~0u, e.x, 0); e.y = __shfl_sync(~0u, e.y, 0);
          if (elect()) mbar_arrive(bar + B_QE + (qi & 1) * 8);
          qi++;
          return e;
        };
        while (true) {
          const uint2 e = pop();
          const int type = e.x & 255;
          if (type == T_END) break;
          const int sl = (e.x >> 8) & 255, kc = (e.x >> 16) & 255, rb = e.x >> 24;
          if (elect()) {
            sts64(sb + SM_DESC + (seq & 3) * 16, e.x, e.y | st | (ph << 8));
            mbar_arrive(bar + B_D + (seq & 3) * 8);
          }
          seq++;
          const int nkb = task_nkb(type, kc), kb0 = type == T_OP ? op_kb0(kc) : kc * 12;
          const uint4* A = type <= T_QA ? g_xnT : type == T_OP ? g_oT : type == T_F1 ? g_hnT : g_gT;
          const int ktot = type == T_OP ? 64 : type == T_F2 ? 72 : 9;
          const uint4* src = A + ((size_t)rb * ktot + kb0) * 1024 + rank * 512;
          bservice();
          for (int kb = 0; kb < nkb; kb++) {
            pwait(bar + B_EA + st * 8, ph);
            if (elect()) {
              mbar_expect(bar + B_FA + st * 8, 16384);
              bulk_mc(sb + SM_A + st * 16384 + rank * 8192, src, 8192, bar + B_FA + st * 8);
            }
            src += 1024;
            if (++st == NS) { st = 0; ph ^= 1; }
          }
          if (type == T_QA) {
            const size_t so = (size_t)sl * NSEG + rb * 4;
            const int mpos = (e.y >> 19) & 1 ? 2 : 4;
            for (int q = 0; q < 5; q++) {
              if (q == 4 && mpos == 4) pop();
              pwait(bar + B_EA + st * 8, ph);
              const uint32_t fa = bar + B_FA + st * 8, dst = sb + SM_A + st * 16384;
              const uint4* p = q < 2 ? g_Kf + so * 512 + q * 1024 : g_Vf + so * 512 + (q - (mpos == 2 ? 3 : 2)) * 1024;
              if (elect()) {
                mbar_expect(fa, 16384);
                if (q != mpos) bulk_g2s(dst, p, 16384, fa);
                else { bulk_g2s(dst, g_Kmf + so * 128, 8192, fa); bulk_g2s(dst + 8192, g_Vmf + so * 128, 8192, fa); }
              }
              if (++st == NS) { st = 0; ph ^= 1; }
            }
          }
        }
        while (th < 3) { bservice(); if (timed_out(t0)) break; }
        if (elect()) {
          for (int i = 0; i < 2; i++) {
            sts64(sb + SM_DESC + ((seq + i) & 3) * 16, T_END, i);
            mbar_arrive(bar + B_D + ((seq + i) & 3) * 8);
          }
        }
      }
      __syncwarp();
      asm volatile("barrier.cluster.arrive.relaxed.aligned; barrier.cluster.wait.aligned;" ::: "memory");
    } else if (w == 1) {
      if (lane == 0) {
        uint32_t fbph = 0;
        int qi = 0, tk = 0, tiles = 0, pubs = 0, pub0 = 0, pub1 = 0;
        auto service = [&]() {
          bool any = false;
          if (mbar_test(bar + B_PD, pub0 & 1)) {
            const uint2 p = lds64(sb + SM_PUB);
            mbar_arrive(bar + B_PE);
            red_release(reinterpret_cast<unsigned*>(((unsigned long long)p.y << 32) | p.x));
            pub0++; pubs++; any = true;
          }
          if (mbar_test(bar + B_PD + 8, pub1 & 1)) {
            const uint2 p = lds64(sb + SM_PUB + 8);
            mbar_arrive(bar + B_PE + 8);
            red_release(reinterpret_cast<unsigned*>(((unsigned long long)p.y << 32) | p.x));
            pub1++; pubs++; any = true;
          }
          return any;
        };
        auto can_post = [&]() { return qi == 0 || mbar_test(bar + B_QE + ((qi - 1) & 1) * 8, ((qi - 1) >> 1) & 1); };
        auto post = [&](uint32_t x, uint32_t y) {
          sts64(sb + SM_TQ + (qi & 1) * 16, x, y);
          mbar_arrive(bar + B_QF + (qi & 1) * 8);
          qi++;
        };
        while (true) {
          unsigned task;
          if (rank == 0) {
            task = atomicAdd(&g_ticket, 1u);
            asm volatile("st.async.shared::cluster.mbarrier::complete_tx::bytes.b32 [%0], %1, [%2];"
              :: "r"(sb + SM_TK + (tk & 3) * 4 + pd), "r"(task), "r"(bar + B_TK + (tk & 3) * 8 + pd) : "memory");
          } else {
            mbar_expect(bar + B_TK + (tk & 3) * 8, 4);
            while (!mbar_test(bar + B_TK + (tk & 3) * 8, (tk >> 2) & 1)) { service(); if (timed_out(t0)) break; }
            asm volatile("ld.shared.b32 %0, [%1];" : "=r"(task) : "r"(sb + SM_TK + (tk & 3) * 4) : "memory");
          }
          tk++;
          if (task >= (unsigned)NTASK) break;
          int type, sl, kc = 0, rb0, n;
          {
            const int e = c_order[task], r = e >> 11;
            type = e & 7; rb0 = (e >> 3) & 15; n = (e >> 7) & 15;
            if (type == 0) { type = rank; sl = r; }
            else {
              if (type & 1) { kc = r / 3; sl = r % 3; } else sl = r;
              sl = 2 * sl + rank;
            }
          }
          const int nkb = task_nkb(type, kc);
          auto deps_ready = [&](int rb, bool mem) -> bool {
            if (mem) return (int)(ld_acquire(&g_memflag[sl * 8]) - (epoch * 64 + rb * 4 + 4)) >= 0;
            if (type == T_QA) return ld_acquire(&g_kvflag[rb * 64 + sl]) == epoch && ld_acquire(&g_kvflag[rb * 64 + 32 + sl]) == epoch;
            if (type == T_OP) return (int)(ld_acquire(&g_cntO[(rb * 8 + kc) * PAD]) - epoch * (nkb >> 1)) >= 0;
            if (type == T_F1) return (int)(ld_acquire(&g_cntH[rb * PAD]) - epoch * 64) >= 0;
            if (type == T_F2) return (int)(ld_acquire(&g_cntG[(rb * 8 + kc) * PAD]) - epoch * 6) >= 0;
            return rb >= rb0 + 2 || (rb == 0 ? (int)(ld_acquire(&g_cntX[0]) - epoch * 4) >= 0 : (int)(ld_acquire(&g_cntX[32]) - epoch * 60) >= 0);
          };
          int t = 0;
          bool bpost = false;
          bool mem = false, rdy = false, mnow = false;
          while (t < n) {
            bool prog = false;
            if (!bpost && (tk == 1 || mbar_test(bar + B_BE, tk & 1))) {
              sts32(sb + SM_RED, type | (sl << 8) | (kc << 16));
              mbar_arrive(bar + B_BF);
              bpost = true; prog = true;
            }
            prog |= service();
            {
              const int rb = rb0 + t;
              if (!rdy && deps_ready(rb, mem)) {
                rdy = true;
                mnow = type == T_QA && !mem && deps_ready(rb, true);
                if (type > T_V || t < 2) asm volatile("fence.proxy.async.global;" ::: "memory");
              }
              if (rdy && bpost && can_post()) {
                post(type | (sl << 8) | (kc << 16) | (rb << 24), ((t == n - 1) << 16) | ((t < 2) << 17) | (fbph << 18) | (mnow << 19));
                rdy = false; prog = true;
                if (!mem) tiles++;
                if (type == T_QA && !mem && !mnow) mem = true; else { mem = false; t++; }
              }
            }
            if (!prog) { if (timed_out(t0)) break; __nanosleep(rdy ? 20 : 80); }
          }
          fbph ^= 1;
        }
        while (!can_post()) { service(); if (timed_out(t0)) break; }
        post(T_END, 0);
        while (pubs < tiles) { if (!service()) { if (timed_out(t0)) break; __nanosleep(20); } }
        finish(epoch);
      }
      __syncwarp();
      asm volatile("barrier.cluster.arrive.relaxed.aligned; barrier.cluster.wait.aligned;" ::: "memory");
    } else {
      const int uq = lane >> 3, j = lane & 3;
      int id = 0;
      if (lane == 0) id = (int)atomicAdd(&g_wticket, 1u);
      id = __shfl_sync(~0u, id, 0);
      int nl = id < 128 ? (id & 1) : NRB, nf = id < 128 ? ((id & 1) ^ 1) : NRB;
      while (nl < NRB || nf < NRB) {
        int fin = 0;
        if (lane == 0) {
          while (true) {
            const int dl = nl < NRB ? (int)(ld_relaxed(&g_cntP1[nl * PAD]) - epoch * 36) : -1000;
            const int df = nf < NRB ? (int)(ld_relaxed(&g_cntP2[nf * PAD]) - epoch * 36) : -1000;
            if (dl >= -PRE) break;
            if (df >= -PRE) { fin = 1; break; }
            if (timed_out(t0)) { fin = nl >= NRB; break; }
            __nanosleep(dl <= -36 && df <= -36 ? 500 : 100);
          }
        }
        fin = __shfl_sync(~0u, fin, 0);
        const int rb = fin ? nf : nl;
        if (fin) nf += 2; else nl += 2;
        const int r2 = rb * 64 + (id >> 1), r8 = r2 >> 2;
        const int cl = (r2 & 3) * 8 + (lane & 7), g = cl >> 2;
        uint4* hp = g_hT + ((size_t)r8 * 18 + uq) * 32 + cl;
        const uint4* p = (fin ? g_p2 : g_p1) + ((size_t)r8 * 18 + uq) * (SPL * 32) + cl;
        const size_t roff = (size_t)(r8 * 8 + g) * (DM / 2) + uq * 16 + j;
        const uint32_t* e = fin ? reinterpret_cast<const uint32_t*>(b2) + uq * 16 + j : reinterpret_cast<const uint32_t*>(x) + roff;
        const bool v4 = uq < 2;
        uint4 hv[5];
#pragma unroll
        for (int t = 0; t < 5; t++) {
          hv[t] = make_uint4(0, 0, 0, 0);
          if (t < 4 || v4) hv[t] = make_uint4(ldg32(e + t * 64), ldg32(e + t * 64 + 4), ldg32(e + t * 64 + 8), ldg32(e + t * 64 + 12));
        }
        if (lane == 0) wait_cnt(fin ? &g_cntP2[rb * PAD] : &g_cntP1[rb * PAD], epoch * 36, 36, t0);
        __syncwarp();
        TR_T(tr0);
        float s = 0.f;
#pragma unroll
        for (int b = 0; b < 2; b++) {
          uint4 v[3][SPL], r[3];
#pragma unroll
          for (int t = 0; t < 3 - b; t++) {
            const int tt = b * 3 + t;
#pragma unroll
            for (int q = 0; q < SPL; q++) { v[t][q] = make_uint4(0, 0, 0, 0); if (tt < 4 || v4) v[t][q] = ldg_cg(p + (tt * 4 * SPL + q) * 32); }
          }
          if (fin) {
#pragma unroll
            for (int t = 0; t < 3 - b; t++) { const int tt = b * 3 + t; r[t] = make_uint4(0, 0, 0, 0); if (tt < 4 || v4) r[t] = ldg_cg(hp + tt * 128); }
          }
#pragma unroll
          for (int t = 0; t < 3 - b; t++) {
            const int tt = b * 3 + t;
            float f[8] = {0.f, 0.f, 0.f, 0.f, 0.f, 0.f, 0.f, 0.f};
#pragma unroll
            for (int q = 0; q < SPL; q++) acc8(f, v[t][q]);
            acc8(f, hv[tt]);
            if (fin) acc8(f, r[t]);
            const uint4 h = make_uint4(pack2(f[0], f[1]), pack2(f[2], f[3]), pack2(f[4], f[5]), pack2(f[6], f[7]));
            hv[tt] = h;
            if (tt < 4 || v4) {
              if (fin) { uint32_t* o = reinterpret_cast<uint32_t*>(out) + roff + tt * 64; o[0] = h.x; o[4] = h.y; o[8] = h.z; o[12] = h.w; }
              else stg128(hp + tt * 128, h.x, h.y, h.z, h.w);
            }
            s += ((bflo(h.x) + bfhi(h.x)) + (bflo(h.y) + bfhi(h.y))) + ((bflo(h.z) + bfhi(h.z)) + (bflo(h.w) + bfhi(h.w)));
          }
        }
        if (!fin) {
          s += __shfl_xor_sync(~0u, s, 1); s += __shfl_xor_sync(~0u, s, 2); s += __shfl_xor_sync(~0u, s, 8); s += __shfl_xor_sync(~0u, s, 16);
          const float mean = s * (1.f / DM);
          float dv[5][8];
          float q = 0.f;
#pragma unroll
          for (int t = 0; t < 5; t++) {
            dv[t][0] = bflo(hv[t].x) - mean; dv[t][1] = bfhi(hv[t].x) - mean; dv[t][2] = bflo(hv[t].y) - mean; dv[t][3] = bfhi(hv[t].y) - mean;
            dv[t][4] = bflo(hv[t].z) - mean; dv[t][5] = bfhi(hv[t].z) - mean; dv[t][6] = bflo(hv[t].w) - mean; dv[t][7] = bfhi(hv[t].w) - mean;
            float qq = 0.f;
#pragma unroll
            for (int i = 0; i < 8; i++) qq = fmaf(dv[t][i], dv[t][i], qq);
            if (t < 4 || v4) q += qq;
          }
          q += __shfl_xor_sync(~0u, q, 1); q += __shfl_xor_sync(~0u, q, 2); q += __shfl_xor_sync(~0u, q, 8); q += __shfl_xor_sync(~0u, q, 16);
          const float rs = rsqrtf(q * (1.f / DM) + 1e-5f);
          uint4* dst = g_hnT + ((size_t)rb * 9 + (uq >> 1)) * 1024 + (r8 & 15) * 64 + ((uq & 1) * 4 + j) * 8 + g;
#pragma unroll
          for (int t = 0; t < 5; t++)
            if (t < 4 || v4)
              stg128(dst + t * 2048, pack2(dv[t][0] * rs, dv[t][1] * rs), pack2(dv[t][2] * rs, dv[t][3] * rs),
                     pack2(dv[t][4] * rs, dv[t][5] * rs), pack2(dv[t][6] * rs, dv[t][7] * rs));
          __syncwarp();
          if (lane == 0) red_release(&g_cntH[rb * PAD]);
        }
        if (lane == 0 && (r2 & 3) == 0) TR_LOG((7 + fin) | ((r8 & 15) << 8) | (rb << 24), tr0, tr0);
      }
      if (lane == 0) finish(epoch);
      __syncwarp();
      asm volatile("barrier.cluster.arrive.relaxed.aligned; barrier.cluster.wait.aligned;" ::: "memory");
    }
  } else {
    asm volatile("setmaxnreg.inc.sync.aligned.u32 %0;" :: "n"(REG_C));
    const int g = lane >> 2, j = lane & 3;
    const int l0 = __shfl_sync(~0u, lane == 0, lane);
    for (int seq = wg;; seq += 2) {
      mbar_wait(bar + B_D + (seq & 3) * 8, (seq >> 2) & 1, t0);
      uint2 d = lds64(sb + SM_DESC + (seq & 3) * 16);
      d.x = __shfl_sync(~0u, d.x, 0); d.y = __shfl_sync(~0u, d.y, 0);
      const int type = d.x & 255;
      const int sl = (d.x >> 8) & 255, kc = (d.x >> 16) & 255, rb = d.x >> 24;
      const int nkb = task_nkb(type, kc);
      const int last = (d.y >> 16) & 1; const bool needb = (d.y >> 17) & 1;
      int st = d.y & 255, ph = ((d.y >> 8) & 1) ^ 1, prev = 0;
      float acc[2][64];
      {
        const uint32_t* bp = reinterpret_cast<const uint32_t*>(b1 + sl * 128) + j;
#pragma unroll
        for (int i = 0; i < 16; i++) {
          uint32_t b = 0;
          if (type == T_F1) b = ldg32(bp + i * 4);
          acc[0][4 * i] = acc[0][4 * i + 2] = acc[1][4 * i] = acc[1][4 * i + 2] = bflo(b);
          acc[0][4 * i + 1] = acc[0][4 * i + 3] = acc[1][4 * i + 1] = acc[1][4 * i + 3] = bfhi(b);
        }
      }
      fence_regs(acc[0]); fence_regs(acc[1]);
      if (seq > 0) bar_sync(3 + wg, 256);
      if (type == T_END) { if (d.y == 0) bar_arrive(3 + (wg ^ 1), 256); break; }
      TR_T(tr0);
      auto mainloop = [&](auto mode) {
        constexpr int MD = decltype(mode)::value;
        constexpr int PER = MD == 2 ? 4 : 3;
        const uint64_t a_hi = make_desc(0, 128, type == T_QA ? 2048 : 1024, 0), b_hi = MD == 2 ? make_desc(0, 16384, 512, 2) : make_desc(0, 24576, 1024, 1);
        const uint32_t a_off = type == T_QA ? 64 : 512;
        bool oka = false;
        int eb = 0, ec = 0;
        int bt = 0, bk = 0;
        for (int kb = 0; kb < nkb; kb++) {
          if (needb && bk == 0) mbar_wait(bar + B_FB + bt * 8, (d.y >> 18) & 1, t0);
          if (!oka) mbar_wait(bar + B_FA + st * 8, ph, t0);
          const uint64_t da = a_hi + ((((sb + SM_A) & 0x3FFFF) >> 4) + st * 1024), db = b_hi + ((((sb + SM_B) & 0x3FFFF) >> 4) + bt * 3072 + bk * (MD == 2 ? 256 : 512));
          if (++bk == PER) { bk = 0; bt++; }
          int nst = st + 1, nph = ph;
          if (nst == NS) { nst = 0; nph ^= 1; }
          wg_fence();
#pragma unroll
          for (int ks = 0; ks < 4; ks++) {
            if (MD == 1) {
              wgmma_n128<1, 0>(acc[0], db + ks * 128, da + ks * 16, 1);
              wgmma_n128<1, 0>(acc[1], db + 1536 + ks * 128, da + ks * 16, 1);
            } else if (MD == 0) {
              wgmma_n128<0, 1>(acc[0], da + ks * 16, db + ks * 128, 1);
              wgmma_n128<0, 1>(acc[1], da + a_off + ks * 16, db + ks * 128, 1);
            } else {
              wgmma_n96<0, 1>(acc[0], da + ks * 16, db + ks * 64, 1);
              wgmma_n96<0, 1>(acc[1], da + 512 + ks * 16, db + ks * 64, 1);
            }
            if (ks == 0) {
              wg_commit();
              wg_wait<1>();
              arrive2_if(bar + B_EA + prev * 8, pd, l0 & (kb > 0), 1);
              mbar_arrive_if(bar + B_EB + eb * 8, l0 & (ec == PER) & last);
              if (ec == PER) { ec = 0; eb++; }
              ec++;
              wg_fence();
            }
            if (ks == 2) {
              if (kb == nkb - 1) { oka = false; if (type != T_QA) bar_arrive(3 + (wg ^ 1), 256); }
              else oka = mbar_test(bar + B_FA + nst * 8, nph);
              wg_fence();
            }
          }
          wg_commit();
          prev = st; st = nst; ph = nph;
        }
        wg_wait<0>();
      };
      if (type == T_V) mainloop(IntC<1>()); else if (type == T_OP || type == T_F2) mainloop(IntC<2>()); else mainloop(IntC<0>());
      arrive2_if(bar + B_EA + prev * 8, pd, l0, 1);
      mbar_arrive_if(bar + B_EB + 16, l0 & last);
      fence_regs(acc[0]); fence_regs(acc[1]);
      TR_T(tr1);
      unsigned* cnt;
      if (type <= T_V) {
        uint4* base = type == T_V ? g_Vf + (((size_t)sl * NSEG + rb * 4) * 8 + w) * 64 + lane : g_Kf + ((size_t)sl * 128 + rb * 8 + w) * 256 + lane;
        const int smb = type == T_V ? 256 : 1024, sq2 = type == T_V ? 512 : 64;
#pragma unroll
        for (int mb = 0; mb < 2; mb++) {
#pragma unroll
          for (int q = 0; q < 8; q++) {
            const float* c = &acc[mb][q * 8];
            stg128(base + mb * smb + (q >> 1) * sq2 + (q & 1) * 32, pack2(c[0], c[1]), pack2(c[2], c[3]), pack2(c[4], c[5]), pack2(c[6], c[7]));
          }
        }
        cnt = &g_kvflag[rb * 64 + type * 32 + sl];
      } else if (type == T_OP || type == T_F2) {
        uint4* base = (type == T_OP ? g_p1 : g_p2) + (((size_t)(rb * 16 + w * 2) * 18 + sl * 3) * SPL + kc) * 32 + lane;
#pragma unroll
        for (int u = 0; u < 3; u++)
#pragma unroll
          for (int mb = 0; mb < 2; mb++)
#pragma unroll
            for (int hi = 0; hi < 2; hi++) {
              const float* c = &acc[mb][u * 16 + hi * 2];
              stg128(base + ((mb * 8 + hi) * 18 + u) * (SPL * 32), pack2(c[0], c[1]), pack2(c[4], c[5]), pack2(c[8], c[9]), pack2(c[12], c[13]));
            }
        cnt = type == T_OP ? &g_cntP1[(rb) * PAD] : &g_cntP2[(rb) * PAD];
      } else if (type == T_F1) {
        uint4* base = g_gT + ((size_t)rb * 72 + sl * 2) * 1024 + w * 128 + j * 8 + g;
#pragma unroll
        for (int u = 0; u < 4; u++) {
          if (F1SPLIT && (d.y >> 28) == u + 1) break;
#pragma unroll
          for (int mb = 0; mb < 2; mb++) {
#pragma unroll
            for (int hi = 0; hi < 2; hi++) {
              uint32_t p[4];
#pragma unroll
              for (int i = 0; i < 4; i++) {
                const float* c = &acc[mb][(u * 4 + i) * 4 + hi * 2];
                p[i] = pack2(gelu_tanh(c[0]), gelu_tanh(c[1]));
              }
              stg128(base + (u >> 1) * 1024 + (mb * 8 + hi) * 64 + (u & 1) * 32, p[0], p[1], p[2], p[3]);
            }
          }
        }
        cnt = &g_cntG[(rb * 8 + sl / 6) * PAD];
      } else {
        uint32_t qa[2][8][4];
#pragma unroll
        for (int mb = 0; mb < 2; mb++)
#pragma unroll
          for (int ks = 0; ks < 8; ks++)
#pragma unroll
            for (int i = 0; i < 4; i++) qa[mb][ks][i] = pack2(acc[mb][ks * 8 + 2 * i], acc[mb][ks * 8 + 2 * i + 1]);
        float sc[2][5][4];
#pragma unroll
        for (int mb = 0; mb < 2; mb++)
#pragma unroll
          for (int n = 0; n < 5; n++) { sc[mb][n][0] = sc[mb][n][1] = sc[mb][n][2] = sc[mb][n][3] = 0.f; }
        auto stg_i = [&](int e) { const int q = st + e; return q >= NS ? q - NS : q; };
        auto stg_p = [&](int e) { return st + e >= NS ? ph ^ 1 : ph; };
        const int ek = w >> 1;
        const int em = (d.y >> 19) & 1 ? 2 : 4, ev = (em == 2 ? 3 : 2) + ek;
        const uint32_t woff = sb + SM_A + (w & 1) * 8192 + lane * 16;
        {
          mbar_wait(bar + B_FA + stg_i(ek) * 8, stg_p(ek), t0);
          const uint32_t ka = woff + stg_i(ek) * 16384;
          uint4 kf[16];
#pragma unroll
          for (int i = 0; i < 16; i++) kf[i] = lds128(ka + i * 512);
#pragma unroll
          for (int ks = 0; ks < 8; ks++) {
#pragma unroll
            for (int mb = 0; mb < 2; mb++) {
              mma16816(sc[mb][0], qa[mb][ks], kf[ks].x, kf[ks].z);
              mma16816(sc[mb][1], qa[mb][ks], kf[ks].y, kf[ks].w);
              mma16816(sc[mb][2], qa[mb][ks], kf[8 + ks].x, kf[8 + ks].z);
              if (mb == 1) mma16816(sc[mb][3], qa[mb][ks], kf[8 + ks].y, kf[8 + ks].w);
            }
          }
          __syncwarp();
          arrive2_if(bar + B_EA + stg_i(ek) * 8, pd, l0, 2);
        }
        uint4 vf[16], km[4], vm[4];
        TR_T(tq0);
        {
          mbar_wait(bar + B_FA + stg_i(em) * 8, stg_p(em), t0);
          const uint32_t ma = sb + SM_A + stg_i(em) * 16384 + w * 2048 + lane * 16;
#pragma unroll
          for (int i = 0; i < 4; i++) km[i] = lds128(ma + i * 512);
          float s2[2][4] = {{0.f, 0.f, 0.f, 0.f}, {0.f, 0.f, 0.f, 0.f}};
#pragma unroll
          for (int u = 0; u < 4; u++) {
#pragma unroll
            for (int mb = 0; mb < 2; mb++) {
              mma16816(sc[mb][4], qa[mb][2 * u], km[u].x, km[u].y);
              mma16816(s2[mb], qa[mb][2 * u + 1], km[u].z, km[u].w);
            }
          }
#pragma unroll
          for (int mb = 0; mb < 2; mb++)
#pragma unroll
            for (int i = 0; i < 4; i++) sc[mb][4][i] += s2[mb][i];
#pragma unroll
          for (int i = 0; i < 4; i++) vm[i] = lds128(ma + 8192 + i * 512);
        }
        const float scl = 0.08838834764831845f * 1.4426950408889634f;
        const float NEG = -INFINITY;
        uint32_t pa[2][5][2];
        float inv[2][2];
#pragma unroll
        for (int mb = 0; mb < 2; mb++) {
#pragma unroll
          for (int hi = 0; hi < 2; hi++) {
            const int nd = mb + 2 * hi;
            if (2 * j > g) sc[mb][nd][hi * 2] = NEG;
            if (2 * j + 1 > g) sc[mb][nd][hi * 2 + 1] = NEG;
            float m = fmaxf(sc[mb][4][hi * 2], sc[mb][4][hi * 2 + 1]);
#pragma unroll
            for (int n = 0; n < 4; n++) if (n <= nd) m = fmaxf(m, fmaxf(sc[mb][n][hi * 2], sc[mb][n][hi * 2 + 1]));
            m = fmaxf(m, __shfl_xor_sync(~0u, m, 1)); m = fmaxf(m, __shfl_xor_sync(~0u, m, 2));
            const float mc = m * scl;
            float l = 0.f;
#pragma unroll
            for (int n = 0; n < 5; n++) {
              if (n <= nd || n == 4) {
                const float e0 = ex2(fmaf(sc[mb][n][hi * 2], scl, -mc)), e1 = ex2(fmaf(sc[mb][n][hi * 2 + 1], scl, -mc));
                l += e0 + e1;
                pa[mb][n][hi] = pack2(e0, e1);
              } else pa[mb][n][hi] = 0u;
            }
            l += __shfl_xor_sync(~0u, l, 1); l += __shfl_xor_sync(~0u, l, 2);
            inv[mb][hi] = __fdividef(1.f, l);
          }
        }
        {
          mbar_wait(bar + B_FA + stg_i(ev) * 8, stg_p(ev), t0);
          const uint32_t va = woff + stg_i(ev) * 16384;
#pragma unroll
          for (int i = 0; i < 16; i++) vf[i] = lds128(va + i * 512);
        }
        asm volatile("" :: "r"(vm[3].w), "r"(vf[15].w) : "memory");
        __syncwarp();
        arrive2_if(bar + B_EA + stg_i(ev) * 8, pd, l0, 2);
        arrive2_if(bar + B_EA + stg_i(em) * 8, pd, l0, 1);
        TR_T(tq1);
        uint32_t op[4][2][2][4];
        uint4* obase = g_oT + ((size_t)rb * 64 + sl * 2) * 1024 + w * 256 + j * 8 + g;
#pragma unroll
        for (int u = 0; u < 4; u++) {
          float o[2][4][4];
#pragma unroll
          for (int mb = 0; mb < 2; mb++) {
#pragma unroll
            for (int i = 0; i < 4; i++) {
              o[mb][i][0] = o[mb][i][1] = o[mb][i][2] = o[mb][i][3] = 0.f;
              const uint4 v0 = vf[(2 * u + (i >> 1)) * 2], v1 = vf[(2 * u + (i >> 1)) * 2 + 1];
              const uint32_t vmw = i == 0 ? vm[u].x : i == 1 ? vm[u].y : i == 2 ? vm[u].z : vm[u].w;
              mma1688(o[mb][i], pa[mb][4][0], pa[mb][4][1], vmw);
              mma16816(o[mb][i], pa[mb][0][0], pa[mb][0][1], pa[mb][1][0], pa[mb][1][1], (i & 1) ? v0.y : v0.x, (i & 1) ? v0.w : v0.z);
              if (mb == 0) mma1688(o[mb][i], pa[mb][2][0], pa[mb][2][1], (i & 1) ? v1.y : v1.x);
              else mma16816(o[mb][i], pa[mb][2][0], pa[mb][2][1], pa[mb][3][0], pa[mb][3][1], (i & 1) ? v1.y : v1.x, (i & 1) ? v1.w : v1.z);
            }
          }
          if (u == 3) bar_arrive(3 + (wg ^ 1), 256);
#pragma unroll
          for (int mb = 0; mb < 2; mb++) {
#pragma unroll
            for (int hi = 0; hi < 2; hi++) {
              const float s = inv[mb][hi];
#pragma unroll
              for (int i = 0; i < 4; i++) op[u][mb][hi][i] = pack2(o[mb][i][hi * 2] * s, o[mb][i][hi * 2 + 1] * s);
            }
          }
        }
        TR_T(tq2);
#pragma unroll
        for (int u = 0; u < 4; u++)
#pragma unroll
          for (int mb = 0; mb < 2; mb++)
#pragma unroll
            for (int hi = 0; hi < 2; hi++)
              stg128(obase + (u >> 1) * 1024 + (mb + 2 * hi) * 64 + (u & 1) * 32, op[u][mb][hi][0], op[u][mb][hi][1], op[u][mb][hi][2], op[u][mb][hi][3]);
        if (tid == wg * 128) TR_LOG(10 | (rb << 24), tq0 - tr1, tq1 - tr1);
        if (tid == wg * 128) TR_LOG(11 | (rb << 24), tq2 - tr1, tr1);
        cnt = &g_cntO[(rb * 8 + (sl < 12 ? sl / 6 : 2 + (sl - 12) / 5)) * PAD];
      }
      mbar_wait(bar + B_PE + wg * 8, ((seq >> 1) & 1) ^ 1, t0);
      if (w == 0 && l0) {
        sts64(sb + SM_PUB + wg * 8, (uint32_t)(uintptr_t)cnt, (uint32_t)((uintptr_t)cnt >> 32));
        TR_LOG(d.x, tr0, tr1);
      }
      __syncwarp();
      mbar_arrive_if(bar + B_PD + wg * 8, l0);
    }
    __syncwarp();
    asm volatile("barrier.cluster.arrive.relaxed.aligned; barrier.cluster.wait.aligned;" ::: "memory");
  }
}
}
typedef CUresult (*EncodeFn)(CUtensorMap*, CUtensorMapDataType, cuuint32_t, void*, const cuuint64_t*, const cuuint64_t*, const cuuint32_t*,
                             const cuuint32_t*, CUtensorMapInterleave, CUtensorMapSwizzle, CUtensorMapL2promotion, CUtensorMapFloatOOBfill);
static EncodeFn get_encode() {
  void* fn = nullptr; cudaDriverEntryPointQueryResult st;
  cudaGetDriverEntryPoint("cuTensorMapEncodeTiled", &fn, cudaEnableDefault, &st);
  return (EncodeFn)fn;
}
static CUtensorMap map2d(EncodeFn enc, const void* p, int rows, int cols, int brow) {
  CUtensorMap m;
  cuuint64_t dim[2] = {(cuuint64_t)cols, (cuuint64_t)rows}; cuuint64_t str[1] = {(cuuint64_t)cols * 2};
  cuuint32_t box[2] = {64, (cuuint32_t)brow}, es[2] = {1, 1};
  enc(&m, CU_TENSOR_MAP_DATA_TYPE_BFLOAT16, 2, (void*)p, dim, str, box, es, CU_TENSOR_MAP_INTERLEAVE_NONE, CU_TENSOR_MAP_SWIZZLE_128B,
      CU_TENSOR_MAP_L2_PROMOTION_L2_256B, CU_TENSOR_MAP_FLOAT_OOB_FILL_NONE);
  return m;
}
static CUtensorMap map5d(EncodeFn enc, const void* p, int rows, int cols, int bcols) {
  CUtensorMap m;
  const cuuint64_t rs = (cuuint64_t)cols * 2;
  cuuint64_t dim[5] = {(cuuint64_t)cols, 2, 4, 4, (cuuint64_t)rows / 32}; cuuint64_t str[4] = {rs, 8 * rs, 2 * rs, 32 * rs};
  cuuint32_t box[5] = {(cuuint32_t)bcols, 2, 4, 4, bcols == 64 ? 6u : 8u}, es[5] = {1, 1, 1, 1, 1};
  enc(&m, CU_TENSOR_MAP_DATA_TYPE_BFLOAT16, 5, (void*)p, dim, str, box, es, CU_TENSOR_MAP_INTERLEAVE_NONE,
      bcols == 64 ? CU_TENSOR_MAP_SWIZZLE_128B : CU_TENSOR_MAP_SWIZZLE_64B,
      CU_TENSOR_MAP_L2_PROMOTION_L2_256B, CU_TENSOR_MAP_FLOAT_OOB_FILL_NONE);
  return m;
}
static CUtensorMap map3d(EncodeFn enc, const void* p, int brows) {
  CUtensorMap m;
  cuuint64_t dim[3] = {64, (cuuint64_t)DM, HD / 64}; cuuint64_t str[2] = {(cuuint64_t)HD * 2, 128};
  cuuint32_t box[3] = {64, (cuuint32_t)brows, 2}, es[3] = {1, 1, 1};
  enc(&m, CU_TENSOR_MAP_DATA_TYPE_BFLOAT16, 3, (void*)p, dim, str, box, es, CU_TENSOR_MAP_INTERLEAVE_NONE, CU_TENSOR_MAP_SWIZZLE_128B,
      CU_TENSOR_MAP_L2_PROMOTION_L2_256B, CU_TENSOR_MAP_FLOAT_OOB_FILL_NONE);
  return m;
}
template <typename... KArgs, typename... Args>
static void launch(void (*k)(KArgs...), int grid, int block, int smem, cudaStream_t s, int cluster, bool pdl, Args... args) {
  cudaLaunchConfig_t cfg = {};
  cfg.gridDim = dim3(grid); cfg.blockDim = dim3(block); cfg.dynamicSmemBytes = smem; cfg.stream = s;
  cudaLaunchAttribute at[2]; int n = 0;
  if (cluster > 1) { at[n].id = cudaLaunchAttributeClusterDimension; at[n].val.clusterDim.x = cluster; at[n].val.clusterDim.y = 1; at[n].val.clusterDim.z = 1; n++; }
  if (pdl) { at[n].id = cudaLaunchAttributeProgrammaticStreamSerialization; at[n].val.programmaticStreamSerializationAllowed = 1; n++; }
  cfg.attrs = at; cfg.numAttrs = n;
  cudaLaunchKernelEx(&cfg, k, KArgs(args)...);
}
struct Ctx {
  mega::Maps maps;
  chain::Maps cmaps;
  mega::WPtr wp;
  cudaStream_t s2; cudaEvent_t evFork, evJoin;
  bool init;
};
static void setup(Ctx& c, void* const* d_in) {
  EncodeFn enc = get_encode();
  c.maps.m[mega::T_K] = map3d(enc, d_in[3], 192); c.maps.m[mega::T_V] = map3d(enc, d_in[4], 192);
  c.maps.m[mega::T_QA] = map3d(enc, d_in[2], 192);
  c.maps.m[mega::T_OP] = map5d(enc, d_in[5], HD, DM, 32); c.maps.m[mega::T_F1] = map5d(enc, d_in[8], DM, FF, 64); c.maps.m[mega::T_F2] = map5d(enc, d_in[10], FF, DM, 32);
  { const int src[6] = {3, 4, 2, 5, 8, 10}; for (int i = 0; i < 6; i++) c.wp.p[i] = (const char*)d_in[src[i]]; }
  c.cmaps.q = map3d(enc, d_in[2], 16); c.cmaps.k = map3d(enc, d_in[3], 16); c.cmaps.v = map3d(enc, d_in[4], 16); c.cmaps.o = map2d(enc, d_in[5], HD, DM, 128);
  cudaFuncSetAttribute(chain::chain_kernel, cudaFuncAttributeNonPortableClusterSizeAllowed, 1);
  cudaFuncSetAttribute(chain::chain_kernel, cudaFuncAttributeMaxDynamicSharedMemorySize, chain::SM_TOTAL);
  cudaFuncSetAttribute(mega::mega_kernel, cudaFuncAttributeMaxDynamicSharedMemorySize, mega::SM_TOTAL);
  cudaFuncAttributes fa;
  cudaFuncGetAttributes(&fa, gate_kernel);
  int lo, hi; cudaDeviceGetStreamPriorityRange(&lo, &hi);
  cudaStreamCreateWithPriority(&c.s2, cudaStreamNonBlocking, hi);
  cudaEventCreateWithFlags(&c.evFork, cudaEventDisableTiming); cudaEventCreateWithFlags(&c.evJoin, cudaEventDisableTiming);
  c.init = true;
}
static Ctx g_ctx;
extern "C" void kernel_launch(void* const* d_in, const int* in_sizes, int n_in, void* d_out, int out_size) {
  Ctx& c = g_ctx;
  if (!c.init) setup(c, d_in);
  const bf16 *x = (const bf16*)d_in[0], *mem0 = (const bf16*)d_in[1], *b1 = (const bf16*)d_in[9], *b2 = (const bf16*)d_in[11];
  bf16* out = (bf16*)d_out;
  cudaStream_t s = cudaStreamPerThread;
  cudaEventRecord(c.evFork, s);
  cudaStreamWaitEvent(c.s2, c.evFork, 0);
  launch(chain::chain_kernel, 64, chain::NTHREADS, chain::SM_TOTAL, c.s2, 16, false, c.cmaps, mem0, x, (const bf16*)d_in[2], (const bf16*)d_in[3], (const bf16*)d_in[4], (const bf16*)d_in[5], 0u);
  cudaEventRecord(c.evJoin, c.s2);
  launch(gate_kernel, 1, 1, 0, s, 1, false);
  launch(mega::mega_kernel, 132, 384, mega::SM_TOTAL, s, 2, true, c.maps, x, b1, b2, out, c.wp);
  cudaStreamWaitEvent(s, c.evJoin, 0);
}
```

```cpp
#include <cuda_runtime.h>
#include <cuda_bf16.h>
#include <cuda.h>
#include <stdint.h>

typedef __nv_bfloat16 bf16;

constexpr int SEQ = 2048, DM = 576, NH = 32, DH = 128, HD = 4096, FF = 4608, NSEG = 64, NRB = 16;

__device__ __align__(1024) uint4 g_Kf[NH * 256 * 4 * 32];
__device__ __align__(1024) uint4 g_Vf[NH * NSEG * 128 * 4];
__device__ __align__(1024) uint4 g_Kmf[NH * NSEG * 4 * 32];
__device__ __align__(1024) uint4 g_Vmf[NH * NSEG * 4 * 32];
__device__ __align__(8192) uint4 g_xch[65 * 512];
__device__ unsigned g_kvflag[NRB * 64];
__device__ unsigned g_memflag[NH * 8];
__device__ __align__(1024) uint4 g_xnT[NRB * 9 * 1024];
__device__ unsigned g_cntX[NRB * 32];
__device__ unsigned g_prog;
__device__ unsigned g_epoch;
__device__ unsigned g_resident;
__device__ unsigned g_err;

__device__ __forceinline__ uint32_t smem_u32(const void* p) { return (uint32_t)__cvta_generic_to_shared(p); }
__device__ __forceinline__ void mbar_init(uint32_t a, int cnt) { asm volatile("mbarrier.init.shared::cta.b64 [%0], %1;" :: "r"(a), "r"(cnt) : "memory"); }
__device__ __forceinline__ void mbar_expect(uint32_t a, int bytes) { asm volatile("mbarrier.arrive.expect_tx.shared::cta.b64 _, [%0], %1;" :: "r"(a), "r"(bytes) : "memory"); }
__device__ __forceinline__ void mbar_arrive(uint32_t a) { asm volatile("mbarrier.arrive.shared::cta.b64 _, [%0];" :: "r"(a) : "memory"); }
__device__ __forceinline__ void mbar_arrive_if(uint32_t a, int p) { asm volatile("{ .reg .pred q; setp.ne.b32 q, %1, 0; @q mbarrier.arrive.shared::cta.b64 _, [%0]; }" :: "r"(a), "r"(p) : "memory"); }
__device__ __forceinline__ bool mbar_try(uint32_t a, uint32_t parity) {
  uint32_t ok;
  asm volatile("{ .reg .pred p; mbarrier.try_wait.parity.shared::cta.b64 p, [%1], %2; selp.u32 %0, 1, 0, p; }" : "=r"(ok) : "r"(a), "r"(parity) : "memory");
  return ok;
}
__device__ __forceinline__ bool mbar_test(uint32_t a, uint32_t parity) {
  uint32_t ok;
  asm volatile("{ .reg .pred p; mbarrier.test_wait.parity.shared::cta.b64 p, [%1], %2; selp.u32 %0, 1, 0, p; }" : "=r"(ok) : "r"(a), "r"(parity) : "memory");
  return ok;
}
__device__ __forceinline__ bool mbar_try_cl(uint32_t a, uint32_t parity) {
  uint32_t ok;
  asm volatile("{ .reg .pred p; mbarrier.try_wait.parity.acquire.cluster.shared::cta.b64 p, [%1], %2; selp.u32 %0, 1, 0, p; }" : "=r"(ok) : "r"(a), "r"(parity) : "memory");
  return ok;
}
__device__ __forceinline__ uint32_t clk32() { uint32_t c; asm volatile("mov.u32 %0, %%clock;" : "=r"(c)); return c; }
constexpr uint32_t TIMEOUT_CLKS = 400000000u;
__device__ __forceinline__ bool timed_out(uint32_t t0) {
  if (clk32() - t0 > TIMEOUT_CLKS) { g_err = 1; return true; }
  return false;
}
__device__ __forceinline__ void mbar_wait(uint32_t a, uint32_t parity, uint32_t t0) {
  if (mbar_try(a, parity)) return;
  while (!mbar_try(a, parity)) { if (timed_out(t0)) break; }
}
__device__ __forceinline__ void mbar_wait_cl(uint32_t a, uint32_t parity, uint32_t t0) {
  while (!mbar_try_cl(a, parity)) { if (timed_out(t0)) break; }
}
__device__ __forceinline__ uint32_t mapa(uint32_t a, uint32_t r) { uint32_t d; asm volatile("mapa.shared::cluster.u32 %0, %1, %2;" : "=r"(d) : "r"(a), "r"(r)); return d; }
__device__ __forceinline__ void st_async16(uint32_t a, uint32_t x, uint32_t y, uint32_t z, uint32_t w, uint32_t bar) {
  asm volatile("st.async.shared::cluster.mbarrier::complete_tx::bytes.v4.b32 [%0], {%1,%2,%3,%4}, [%5];" :: "r"(a), "r"(x), "r"(y), "r"(z), "r"(w), "r"(bar) : "memory");
}
__device__ __forceinline__ void st_async8(uint32_t a, uint32_t x, uint32_t y, uint32_t bar) {
  asm volatile("st.async.shared::cluster.mbarrier::complete_tx::bytes.v2.b32 [%0], {%1,%2}, [%3];" :: "r"(a), "r"(x), "r"(y), "r"(bar) : "memory");
}
__device__ __forceinline__ void bar_sync(int id, int n) { asm volatile("bar.sync %0, %1;" :: "r"(id), "r"(n) : "memory"); }
__device__ __forceinline__ void bar_arrive(int id, int n) { asm volatile("bar.arrive %0, %1;" :: "r"(id), "r"(n) : "memory"); }
__device__ __forceinline__ void cluster_sync() { asm volatile("barrier.cluster.arrive.release.aligned; barrier.cluster.wait.acquire.aligned;" ::: "memory"); }
__device__ __forceinline__ uint32_t pack2(float lo, float hi) { uint32_t d; asm("cvt.rn.bf16x2.f32 %0, %1, %2;" : "=r"(d) : "f"(hi), "f"(lo)); return d; }
__device__ __forceinline__ float bflo(uint32_t v) { return __uint_as_float(v << 16); }
__device__ __forceinline__ float bfhi(uint32_t v) { return __uint_as_float(v & 0xffff0000u); }
__device__ __forceinline__ uint32_t movmat(uint32_t a) { uint32_t d; asm volatile("movmatrix.sync.aligned.m8n8.trans.b16 %0, %1;" : "=r"(d) : "r"(a)); return d; }
__device__ __forceinline__ uint32_t hadd2bf(uint32_t a, uint32_t b) { uint32_t d; asm("add.rn.bf16x2 %0, %1, %2;" : "=r"(d) : "r"(a), "r"(b)); return d; }
__device__ __forceinline__ void mma16816(float (&c)[4], uint32_t a0, uint32_t a1, uint32_t a2, uint32_t a3, uint32_t b0, uint32_t b1) {
  asm volatile("mma.sync.aligned.m16n8k16.row.col.f32.bf16.bf16.f32 {%0,%1,%2,%3}, {%4,%5,%6,%7}, {%8,%9}, {%0,%1,%2,%3};"
    : "+f"(c[0]), "+f"(c[1]), "+f"(c[2]), "+f"(c[3]) : "r"(a0), "r"(a1), "r"(a2), "r"(a3), "r"(b0), "r"(b1));
}
__device__ __forceinline__ void mma16816(float (&c)[4], const uint32_t (&a)[4], uint32_t b0, uint32_t b1) { mma16816(c, a[0], a[1], a[2], a[3], b0, b1); }
__device__ __forceinline__ void mma1688(float (&c)[4], uint32_t a0, uint32_t a1, uint32_t b0) {
  asm volatile("mma.sync.aligned.m16n8k8.row.col.f32.bf16.bf16.f32 {%0,%1,%2,%3}, {%4,%5}, {%6}, {%0,%1,%2,%3};"
    : "+f"(c[0]), "+f"(c[1]), "+f"(c[2]), "+f"(c[3]) : "r"(a0), "r"(a1), "r"(b0));
}
__device__ __forceinline__ void ldsm4t(uint32_t (&r)[4], uint32_t a) {
  asm volatile("ldmatrix.sync.aligned.m8n8.x4.trans.shared.b16 {%0,%1,%2,%3}, [%4];" : "=r"(r[0]), "=r"(r[1]), "=r"(r[2]), "=r"(r[3]) : "r"(a) : "memory");
}
__device__ __forceinline__ uint4 lds128(uint32_t a) { uint4 v; asm volatile("ld.shared.v4.b32 {%0,%1,%2,%3}, [%4];" : "=r"(v.x), "=r"(v.y), "=r"(v.z), "=r"(v.w) : "r"(a) : "memory"); return v; }
__device__ __forceinline__ uint2 lds64(uint32_t a) { uint2 v; asm volatile("ld.shared.v2.b32 {%0,%1}, [%2];" : "=r"(v.x), "=r"(v.y) : "r"(a) : "memory"); return v; }
__device__ __forceinline__ void sts128(uint32_t a, uint32_t x, uint32_t y, uint32_t z, uint32_t w) { asm volatile("st.shared.v4.b32 [%0], {%1,%2,%3,%4};" :: "r"(a), "r"(x), "r"(y), "r"(z), "r"(w) : "memory"); }
__device__ __forceinline__ void sts64(uint32_t a, uint32_t x, uint32_t y) { asm volatile("st.shared.v2.b32 [%0], {%1,%2};" :: "r"(a), "r"(x), "r"(y) : "memory"); }
__device__ __forceinline__ void sts32(uint32_t a, uint32_t x) { asm volatile("st.shared.b32 [%0], %1;" :: "r"(a), "r"(x) : "memory"); }
__device__ __forceinline__ void cp_async16(uint32_t dst, const void* src) { asm volatile("cp.async.cg.shared.global [%0], [%1], 16;" :: "r"(dst), "l"(src) : "memory"); }
__device__ __forceinline__ void cp_async_wait_all() { asm volatile("cp.async.wait_all;" ::: "memory"); }
__device__ __forceinline__ uint4 ldg_cg(const void* p) { uint4 v; asm volatile("ld.global.cg.v4.b32 {%0,%1,%2,%3}, [%4];" : "=r"(v.x), "=r"(v.y), "=r"(v.z), "=r"(v.w) : "l"(p) : "memory"); return v; }
__device__ __forceinline__ uint4 ld_relaxed16(const void* p) { uint4 v; asm volatile("ld.relaxed.gpu.global.v4.b32 {%0,%1,%2,%3}, [%4];" : "=r"(v.x), "=r"(v.y), "=r"(v.z), "=r"(v.w) : "l"(p) : "memory"); return v; }
__device__ __forceinline__ void st_relaxed16(void* p, uint32_t x, uint32_t y, uint32_t z, uint32_t w) { asm volatile("st.relaxed.gpu.global.v4.b32 [%0], {%1,%2,%3,%4};" :: "l"(p), "r"(x), "r"(y), "r"(z), "r"(w) : "memory"); }
__device__ __forceinline__ unsigned ld_acquire(const unsigned* p) { unsigned v; asm volatile("ld.acquire.gpu.global.u32 %0, [%1];" : "=r"(v) : "l"(p) : "memory"); return v; }
__device__ __forceinline__ uint32_t ldg32(const void* p) { uint32_t v; asm volatile("ld.global.nc.b32 %0, [%1];" : "=r"(v) : "l"(p)); return v; }
__device__ __forceinline__ uint2 ld_relaxed8(const unsigned* p) { uint2 v; asm volatile("ld.relaxed.gpu.global.v2.u32 {%0,%1}, [%2];" : "=r"(v.x), "=r"(v.y) : "l"(p) : "memory"); return v; }
__device__ __forceinline__ unsigned ld_relaxed(const unsigned* p) { unsigned v; asm volatile("ld.relaxed.gpu.global.u32 %0, [%1];" : "=r"(v) : "l"(p) : "memory"); return v; }
__device__ __forceinline__ void st_release(unsigned* p, unsigned v) { asm volatile("st.release.gpu.global.u32 [%0], %1;" :: "l"(p), "r"(v) : "memory"); }
__device__ __forceinline__ float ex2(float x) { float y; asm("ex2.approx.ftz.f32 %0, %1;" : "=f"(y) : "f"(x)); return y; }

__device__ __forceinline__ void st_b128(void* p, uint32_t x, uint32_t y, uint32_t z, uint32_t w) {
  asm volatile("{ .reg .b128 t; .reg .b64 lo, hi; mov.b64 lo, {%1,%2}; mov.b64 hi, {%3,%4}; mov.b128 t, {lo,hi}; st.relaxed.gpu.global.b128 [%0], t; }"
    :: "l"(p), "r"(x), "r"(y), "r"(z), "r"(w) : "memory");
}
__device__ __forceinline__ uint4 ld_b128(const void* p) {
  uint4 v;
  asm volatile("{ .reg .b128 t; .reg .b64 lo, hi; ld.relaxed.gpu.global.b128 t, [%4]; mov.b128 {lo,hi}, t; mov.b64 {%0,%1}, lo; mov.b64 {%2,%3}, hi; }"
    : "=r"(v.x), "=r"(v.y), "=r"(v.z), "=r"(v.w) : "l"(p) : "memory");
  return v;
}
__device__ __forceinline__ void wg_fence() { asm volatile("wgmma.fence.sync.aligned;" ::: "memory"); }
__device__ __forceinline__ void wg_commit() { asm volatile("wgmma.commit_group.sync.aligned;" ::: "memory"); }
template <int N> __device__ __forceinline__ void wg_wait() { asm volatile("wgmma.wait_group.sync.aligned %0;" :: "n"(N) : "memory"); }
__device__ __forceinline__ uint64_t make_desc(uint32_t addr, uint32_t lbo, uint32_t sbo, uint32_t mode) {
  return (uint64_t)((addr & 0x3FFFF) >> 4) | ((uint64_t)(lbo >> 4) << 16) | ((uint64_t)(sbo >> 4) << 32) | ((uint64_t)mode << 62);
}
__device__ __forceinline__ void tma2d(uint32_t dst, const CUtensorMap* m, int c0, int c1, uint32_t bar) {
  asm volatile("cp.async.bulk.tensor.2d.shared::cluster.global.mbarrier::complete_tx::bytes [%0], [%1, {%3, %4}], [%2];"
    :: "r"(dst), "l"(m), "r"(bar), "r"(c0), "r"(c1) : "memory");
}
__device__ __forceinline__ bool elect() {
  uint32_t p; asm volatile("{ .reg .pred q; elect.sync _|q, 0xffffffff; selp.u32 %0, 1, 0, q; }" : "=r"(p)); return p;
}
__device__ __forceinline__ void tma3d(uint32_t dst, const CUtensorMap* m, int c1, int c2, uint32_t bar) {
  asm volatile("cp.async.bulk.tensor.3d.shared::cluster.global.mbarrier::complete_tx::bytes [%0], [%1, {%5, %3, %4}], [%2];"
    :: "r"(dst), "l"(m), "r"(bar), "r"(c1), "r"(c2), "r"(0) : "memory");
}
__device__ __forceinline__ void tma5d(uint32_t dst, const CUtensorMap* m, int c0, int c4, uint32_t bar) {
  asm volatile("cp.async.bulk.tensor.5d.shared::cluster.global.mbarrier::complete_tx::bytes [%0], [%1, {%3, %5, %5, %5, %4}], [%2];"
    :: "r"(dst), "l"(m), "r"(bar), "r"(c0), "r"(c4), "r"(0) : "memory");
}
__device__ __forceinline__ void bulk_g2s(uint32_t dst, const void* src, uint32_t bytes, uint32_t bar) {
  asm volatile("cp.async.bulk.shared::cluster.global.mbarrier::complete_tx::bytes [%0], [%1], %2, [%3];" :: "r"(dst), "l"(src), "r"(bytes), "r"(bar) : "memory");
}
__device__ __forceinline__ void push_dsmem(uint32_t dst, uint32_t src, uint32_t bytes, uint32_t bar, bool on) {
  asm volatile("fence.proxy.async.shared::cta;" ::: "memory");
  __syncwarp();
  if (on && elect())
    asm volatile("cp.async.bulk.shared::cluster.shared::cta.mbarrier::complete_tx::bytes [%0], [%1], %2, [%3];" :: "r"(dst), "r"(src), "r"(bytes), "r"(bar) : "memory");
}
__device__ __forceinline__ uint64_t pol_first() { uint64_t p; asm volatile("createpolicy.fractional.L2::evict_first.b64 %0, 1.0;" : "=l"(p)); return p; }
__device__ __forceinline__ void stg128_h(void* p, uint32_t x, uint32_t y, uint32_t z, uint32_t w, uint64_t pol) {
  asm volatile("st.global.L2::cache_hint.v4.b32 [%0], {%1,%2,%3,%4}, %5;" :: "l"(p), "r"(x), "r"(y), "r"(z), "r"(w), "l"(pol) : "memory");
}
__device__ __forceinline__ uint4 ldg_cg_h(const void* p, uint64_t pol) {
  uint4 v; asm volatile("ld.global.cg.L2::cache_hint.v4.b32 {%0,%1,%2,%3}, [%4], %5;" : "=r"(v.x), "=r"(v.y), "=r"(v.z), "=r"(v.w) : "l"(p), "l"(pol) : "memory"); return v;
}
__device__ __forceinline__ void bulk_g2s_h(uint32_t dst, const void* src, uint32_t bytes, uint32_t bar, uint64_t pol) {
  asm volatile("cp.async.bulk.shared::cluster.global.mbarrier::complete_tx::bytes.L2::cache_hint [%0], [%1], %2, [%3], %4;" :: "r"(dst), "l"(src), "r"(bytes), "r"(bar), "l"(pol) : "memory");
}
__device__ __forceinline__ void stg128(void* p, uint32_t x, uint32_t y, uint32_t z, uint32_t w) {
  asm volatile("st.global.v4.b32 [%0], {%1,%2,%3,%4};" :: "l"(p), "r"(x), "r"(y), "r"(z), "r"(w) : "memory");
}
template <int N> __device__ __forceinline__ void fence_regs(float (&d)[N]) {
#pragma unroll
  for (int i = 0; i < N; i++) asm volatile("" : "+f"(d[i]) :: "memory");
}

#define TR_T(v)
#define TR_VAR(v)
#define TR_SET(v)
#define TR_LOG(info, a, b)
template <int TA, int TB>
__device__ __forceinline__ void wgmma_n96(float (&d)[64], uint64_t da, uint64_t db, int scale_d) {
  asm volatile("{ .reg .pred p; setp.ne.b32 p, %50, 0;\n"
    "wgmma.mma_async.sync.aligned.m64n96k16.f32.bf16.bf16 {%0, %1, %2, %3, %4, %5, %6, %7, %8, %9, %10, %11, %12, %13, %14, %15, %16, %17, %18, %19, %20, %21, %22, %23, %24, %25, %26, %27, %28, %29, %30, %31, %32, %33, %34, %35, %36, %37, %38, %39, %40, %41, %42, %43, %44, %45, %46, %47}, %48, %49, p, 1, 1, %51, %52; }"
    : "+f"(d[0]), "+f"(d[1]), "+f"(d[2]), "+f"(d[3]), "+f"(d[4]), "+f"(d[5]), "+f"(d[6]), "+f"(d[7]), "+f"(d[8]), "+f"(d[9]), "+f"(d[10]), "+f"(d[11]), "+f"(d[12]), "+f"(d[13]), "+f"(d[14]), "+f"(d[15]), "+f"(d[16]), "+f"(d[17]), "+f"(d[18]), "+f"(d[19]), "+f"(d[20]), "+f"(d[21]), "+f"(d[22]), "+f"(d[23]), "+f"(d[24]), "+f"(d[25]), "+f"(d[26]), "+f"(d[27]), "+f"(d[28]), "+f"(d[29]), "+f"(d[30]), "+f"(d[31]), "+f"(d[32]), "+f"(d[33]), "+f"(d[34]), "+f"(d[35]), "+f"(d[36]), "+f"(d[37]), "+f"(d[38]), "+f"(d[39]), "+f"(d[40]), "+f"(d[41]), "+f"(d[42]), "+f"(d[43]), "+f"(d[44]), "+f"(d[45]), "+f"(d[46]), "+f"(d[47])
    : "l"(da), "l"(db), "r"(scale_d), "n"(TA), "n"(TB));
}
template <int TA, int TB>
__device__ __forceinline__ void wgmma_n128(float (&d)[64], uint64_t da, uint64_t db, int scale_d) {
  asm volatile("{ .reg .pred p; setp.ne.b32 p, %66, 0;\n"
    "wgmma.mma_async.sync.aligned.m64n128k16.f32.bf16.bf16 {%0, %1, %2, %3, %4, %5, %6, %7, %8, %9, %10, %11, %12, %13, %14, %15, %16, %17, %18, %19, %20, %21, %22, %23, %24, %25, %26, %27, %28, %29, %30, %31, %32, %33, %34, %35, %36, %37, %38, %39, %40, %41, %42, %43, %44, %45, %46, %47, %48, %49, %50, %51, %52, %53, %54, %55, %56, %57, %58, %59, %60, %61, %62, %63}, %64, %65, p, 1, 1, %67, %68; }"
    : "+f"(d[0]), "+f"(d[1]), "+f"(d[2]), "+f"(d[3]), "+f"(d[4]), "+f"(d[5]), "+f"(d[6]), "+f"(d[7]), "+f"(d[8]), "+f"(d[9]), "+f"(d[10]), "+f"(d[11]), "+f"(d[12]), "+f"(d[13]), "+f"(d[14]), "+f"(d[15]), "+f"(d[16]), "+f"(d[17]), "+f"(d[18]), "+f"(d[19]), "+f"(d[20]), "+f"(d[21]), "+f"(d[22]), "+f"(d[23]), "+f"(d[24]), "+f"(d[25]), "+f"(d[26]), "+f"(d[27]), "+f"(d[28]), "+f"(d[29]), "+f"(d[30]), "+f"(d[31]), "+f"(d[32]), "+f"(d[33]), "+f"(d[34]), "+f"(d[35]), "+f"(d[36]), "+f"(d[37]), "+f"(d[38]), "+f"(d[39]), "+f"(d[40]), "+f"(d[41]), "+f"(d[42]), "+f"(d[43]), "+f"(d[44]), "+f"(d[45]), "+f"(d[46]), "+f"(d[47]), "+f"(d[48]), "+f"(d[49]), "+f"(d[50]), "+f"(d[51]), "+f"(d[52]), "+f"(d[53]), "+f"(d[54]), "+f"(d[55]), "+f"(d[56]), "+f"(d[57]), "+f"(d[58]), "+f"(d[59]), "+f"(d[60]), "+f"(d[61]), "+f"(d[62]), "+f"(d[63])
    : "l"(da), "l"(db), "r"(scale_d), "n"(TA), "n"(TB));
}
__device__ __align__(1024) uint4 g_hnT[NRB * 9 * 1024];
__device__ __align__(1024) uint4 g_oT[NRB * 64 * 1024];
__device__ __align__(1024) uint4 g_gT[NRB * 72 * 1024];
constexpr int MAXSPLIT = 6;
__device__ __align__(1024) uint4 g_p1[MAXSPLIT * 256 * 18 * 32];
__device__ __align__(1024) uint4 g_p2[MAXSPLIT * 256 * 18 * 32];
__device__ __align__(1024) uint4 g_hT[256 * 18 * 32];

constexpr int PAD = 32;
__device__ unsigned g_cntO[NRB * 8 * PAD], g_cntP1[NRB * PAD], g_cntH[NRB * PAD], g_cntG[NRB * 8 * PAD], g_cntP2[NRB * PAD], g_done;
__device__ __forceinline__ void acc8(float (&f)[8], const uint4& v) {
  f[0] += bflo(v.x); f[1] += bfhi(v.x); f[2] += bflo(v.y); f[3] += bfhi(v.y);
  f[4] += bflo(v.z); f[5] += bfhi(v.z); f[6] += bflo(v.w); f[7] += bfhi(v.w);
}

constexpr int SPL = 6;
#define TAILW 16
template <int NB>
__device__ __forceinline__ void row_job(int fin, int r2, int lane, const bf16* __restrict__ x, const bf16* __restrict__ b2, bf16* __restrict__ out,
                                        unsigned epoch, uint32_t t0, bool live) {
  const int uq = lane >> 3, j = lane & 3, r8 = r2 >> 2, rb = r2 >> 6;
  const int cl = (r2 & 3) * 8 + (lane & 7), g = cl >> 2;
  const uint64_t pw = pol_first();
  uint4* hp = g_hT + ((size_t)r8 * 18 + uq) * 32 + cl;
  const uint4* p = (fin ? g_p2 : g_p1) + ((size_t)r8 * 18 + uq) * (SPL * 32) + cl;
  const size_t roff = (size_t)(r8 * 8 + g) * (DM / 2) + uq * 16 + j;
  const uint32_t* e = fin ? reinterpret_cast<const uint32_t*>(b2) + uq * 16 + j : reinterpret_cast<const uint32_t*>(x) + roff;
  const bool v4 = uq < 2;
  uint4 hv[5];
#pragma unroll
  for (int t = 0; t < 5; t++) {
    hv[t] = make_uint4(0, 0, 0, 0);
    if (t < 4 || v4) hv[t] = make_uint4(ldg32(e + t * 64), ldg32(e + t * 64 + 4), ldg32(e + t * 64 + 8), ldg32(e + t * 64 + 12));
  }
  if (lane == 0 && live) {
    const unsigned* cp = fin ? &g_cntP2[rb * PAD] : &g_cntP1[rb * PAD];
    while ((int)(ld_relaxed(cp) - epoch * 36) < (NB == 1 ? -3 : 0)) { if (timed_out(t0)) break; __nanosleep(40); }
    while ((int)(ld_acquire(cp) - epoch * 36) < 0) { if (timed_out(t0)) break; }
  }
  __syncwarp();
  TR_T(tr0);
  const float ps = fin ? 0.5f : 1.f;
  float s = 0.f;
#pragma unroll
  for (int b = 0; b < NB; b++) {
    constexpr int PB = NB == 1 ? 5 : 3;
    uint4 v[PB][SPL], r[PB];
#pragma unroll
    for (int t = 0; t < PB; t++) {
      const int tt = b * PB + t;
      if (tt < 5) {
#pragma unroll
        for (int q = 0; q < SPL; q++) { v[t][q] = make_uint4(0, 0, 0, 0); if ((tt < 4 || v4) && live) v[t][q] = ldg_cg_h(p + (tt * 4 * SPL + q) * 32, pw); }
        r[t] = make_uint4(0, 0, 0, 0);
        if (fin && (tt < 4 || v4) && live) r[t] = ldg_cg(hp + tt * 128);
      }
    }
#pragma unroll
    for (int t = 0; t < PB; t++) {
      const int tt = b * PB + t;
      if (tt < 5) {
        float f[8] = {0.f, 0.f, 0.f, 0.f, 0.f, 0.f, 0.f, 0.f};
#pragma unroll
        for (int q = 0; q < SPL; q++) acc8(f, v[t][q]);
#pragma unroll
        for (int i = 0; i < 8; i++) f[i] *= ps;
        acc8(f, hv[tt]);
        acc8(f, r[t]);
        const uint4 h = make_uint4(pack2(f[0], f[1]), pack2(f[2], f[3]), pack2(f[4], f[5]), pack2(f[6], f[7]));
        hv[tt] = h;
        if ((tt < 4 || v4) && live) {
          if (fin) { uint32_t* o = reinterpret_cast<uint32_t*>(out) + roff + tt * 64; o[0] = h.x; o[4] = h.y; o[8] = h.z; o[12] = h.w; }
          else stg128(hp + tt * 128, h.x, h.y, h.z, h.w);
        }
        s += ((bflo(h.x) + bfhi(h.x)) + (bflo(h.y) + bfhi(h.y))) + ((bflo(h.z) + bfhi(h.z)) + (bflo(h.w) + bfhi(h.w)));
      }
    }
  }
  if (!fin) {
    s += __shfl_xor_sync(~0u, s, 1); s += __shfl_xor_sync(~0u, s, 2); s += __shfl_xor_sync(~0u, s, 8); s += __shfl_xor_sync(~0u, s, 16);
    const float mean = s * (1.f / DM);
    float dv[5][8];
    float q = 0.f;
#pragma unroll
    for (int t = 0; t < 5; t++) {
      dv[t][0] = bflo(hv[t].x) - mean; dv[t][1] = bfhi(hv[t].x) - mean; dv[t][2] = bflo(hv[t].y) - mean; dv[t][3] = bfhi(hv[t].y) - mean;
      dv[t][4] = bflo(hv[t].z) - mean; dv[t][5] = bfhi(hv[t].z) - mean; dv[t][6] = bflo(hv[t].w) - mean; dv[t][7] = bfhi(hv[t].w) - mean;
      float qq = 0.f;
#pragma unroll
      for (int i = 0; i < 8; i++) qq = fmaf(dv[t][i], dv[t][i], qq);
      if (t < 4 || v4) q += qq;
    }
    q += __shfl_xor_sync(~0u, q, 1); q += __shfl_xor_sync(~0u, q, 2); q += __shfl_xor_sync(~0u, q, 8); q += __shfl_xor_sync(~0u, q, 16);
    const float rs = rsqrtf(q * (1.f / DM) + 1e-5f);
    uint4* dst = g_hnT + ((size_t)rb * 9 + (uq >> 1)) * 1024 + (r8 & 15) * 64 + ((uq & 1) * 4 + j) * 8 + g;
#pragma unroll
    for (int t = 0; t < 5; t++)
      if ((t < 4 || v4) && live)
        stg128(dst + t * 2048, pack2(dv[t][0] * rs, dv[t][1] * rs), pack2(dv[t][2] * rs, dv[t][3] * rs),
               pack2(dv[t][4] * rs, dv[t][5] * rs), pack2(dv[t][6] * rs, dv[t][7] * rs));
    __syncwarp();
    if (lane == 0 && live) asm volatile("red.release.gpu.global.add.u32 [%0], 1;" :: "l"(&g_cntH[rb * PAD]) : "memory");
  }
  if (lane == 0 && (r2 & 3) == 0 && live) TR_LOG((7 + fin) | ((r8 & 15) << 8) | (rb << 24), tr0, tr0);
}
#define POLL_MODE 1
#define STAGGER 0
#define WEARLY 6
#define WLATE 1
#define PREF 0
#define CREG 216
#define AREG 72
#define KEEPALIVE 150
#define OWNMMA 0
#define WXE 4
#define PREF_M0 2
#define BULK 0
#define POLL_DELAY 120
#define STICKY 0
#define POLL_GAP 100
#define QDELAY 6000
#define POLL_REP 1
namespace chain {
constexpr int SLOT = 4096;
constexpr int NX = 8;
constexpr int NPV = 9;
constexpr int NV2 = 18 - NPV;
constexpr int NPERM = 2 * (18 - NX) + NPV;
constexpr int SM_X = 0;
constexpr int SM_V2 = SM_X + 2 * NX * SLOT;
constexpr int SM_KX = SM_V2 + NV2 * SLOT;
constexpr int SM_VX = SM_KX + 8192;
constexpr int SM_WO = SM_VX + 8192;
static_assert(SM_WO == NPERM * SLOT, "staging area = X + V2 + KX + VX");
constexpr int SM_MEM = SM_WO + 5 * 16384;
constexpr int SM_OQK = SM_MEM + 9 * 512;
constexpr int SM_XQK = SM_OQK + 4096;
constexpr int SM_OV = SM_XQK + 4096;
constexpr int SM_XV = SM_OV + 2048;
constexpr int SM_S = SM_XV + 2048;
constexpr int SM_O = SM_S + 1536;
constexpr int SM_RS = SM_O + 2048;
constexpr int SM_MB = SM_RS + 8 * 576;
constexpr int SM_INV = SM_MB + 3 * 1152;
constexpr int SM_BAR = SM_INV + 128;
constexpr int SM_PROF = SM_BAR + 128;
constexpr int SM_TOTAL = SM_PROF + 256;
static_assert(SM_TOTAL <= 232448, "smem");
constexpr int B_AG = 0  , B_XQK = 40, B_XV = 48, B_RS = 56, B_KV = 64, B_L = 72, B_W = 80  ;
constexpr int RS_BYTES = 7 * 512 + 8 * 64;
constexpr int BAR_OQK = 1, BAR_S = 2, BAR_O = 3, BAR_ALL = 4, BAR_KVF = 5, BAR_AB = 6, BAR_AB2 = 7, BAR_C = 8;
constexpr int NTHREADS = 384;
constexpr int REG_C = CREG, REG_A = AREG;
static_assert(2 * REG_C + REG_A <= 504, "register pool");

#define PROF(slot) do {} while (0)
#define PROFN(slot) do {} while (0)
#define PROFS() do {} while (0)
#define PROF0(slot) do {} while (0)
#define PROF1(slot) do {} while (0)

struct Maps { CUtensorMap q, k, v, o; };

__device__ __forceinline__ void mmaq(float (&c)[4], const uint4& a, uint32_t b0, uint32_t b1) { mma16816(c, a.x, a.y, a.z, a.w, b0, b1); }
__device__ __forceinline__ int opaque(int v) { int d; asm volatile("mov.u32 %0, %1;" : "=r"(d) : "r"(v)); return d; }
__device__ __forceinline__ uint32_t dep(uint32_t base, uint32_t v, uint32_t zero) {
  uint32_t d; asm("lop3.b32 %0, %1, %2, %3, 0xF8;" : "=r"(d) : "r"(base), "r"(v), "r"(zero)); return d;
}
__device__ __forceinline__ uint32_t frag_off(int lane, int cp) {
  const int mat = lane >> 3, r = lane & 7;
  return ((mat >> 1) * 8 + r) * 128 + (((cp * 2 + (mat & 1)) ^ r) * 16);
}

template <bool EXTRA>
__device__ __forceinline__ void softmax_pv(int s, int x, uint32_t sb, uint32_t sl, uint32_t bar, int lane_in, int a, int head, uint32_t t0,
                                           uint32_t (&WX)[8][4], uint4& vm_out, int P) {
  const int lane = opaque(lane_in);
  uint4* const vm_ptr = g_Vmf + (size_t)head * NSEG * 128 + x * 32 + lane;
  const float sc = 0.08838834764831845f * 1.4426950408889634f;
  const uint32_t wa = sb + SM_WO + 4 * 16384 + frag_off(lane, x);
  bar_sync(BAR_S, 128);
  const uint4 s0 = lds128(sl + SM_S), s1 = lds128(sl + SM_S + 512), s2 = lds128(sl + SM_S + 1024);
  uint4 vx[4];
#pragma unroll
  for (int u = 0; u < 4; u++) vx[u] = lds128(sl + SM_VX + x * 2048 + u * 512);
  const bool okv = mbar_try(bar + B_XV, s & 1);
  const uint32_t lv = sb + x * 512 + lane * 8;
  float y[10] = {__uint_as_float(s0.x), __uint_as_float(s0.y), __uint_as_float(s0.z), __uint_as_float(s0.w),
                 __uint_as_float(s1.x), __uint_as_float(s1.y), __uint_as_float(s1.z), __uint_as_float(s1.w),
                 __uint_as_float(s2.x) + __uint_as_float(s2.z), __uint_as_float(s2.y) + __uint_as_float(s2.w)};
  float m = fmaxf(fmaxf(fmaxf(y[0], y[1]), fmaxf(y[2], y[3])), fmaxf(fmaxf(y[4], y[5]), fmaxf(y[6], y[7])));
  m = fmaxf(m, fmaxf(y[8], y[9]));
  if (P) PROF(12);
  m = fmaxf(m, __shfl_xor_sync(0xffffffffu, m, 1));
  m = fmaxf(m, __shfl_xor_sync(0xffffffffu, m, 2));
  if (!okv) mbar_wait(bar + B_XV, s & 1, t0);
  const uint2 ov0 = lds64(lv + SM_OV), xv0 = lds64(lv + SM_XV), ov1 = lds64(lv + SM_OV + 256), xv1 = lds64(lv + SM_XV + 256);
  if (EXTRA) {
#pragma unroll
    for (int u = 0; u < WXE; u++) ldsm4t(WX[u], wa + u * 2048);
  }
  const float mc = m * sc;
#pragma unroll
  for (int i = 0; i < 10; i++) y[i] = ex2(fmaf(y[i], sc, -mc));
  const uint32_t p0 = pack2(y[0], y[1]), p1 = pack2(y[2], y[3]), p2 = pack2(y[4], y[5]), p3 = pack2(y[6], y[7]), p4 = pack2(y[8], y[9]);
  const uint4 vm = make_uint4(hadd2bf(ov0.x, xv0.x), hadd2bf(ov0.y, xv0.y), hadd2bf(ov1.x, xv1.x), hadd2bf(ov1.y, xv1.y));
  float o0[4] = {0.f, 0.f, 0.f, 0.f}, o1[4] = {0.f, 0.f, 0.f, 0.f}, o2[4] = {0.f, 0.f, 0.f, 0.f}, o3[4] = {0.f, 0.f, 0.f, 0.f};
  mmaq(o0, vx[0], p0, p1); mmaq(o2, vx[2], p0, p1);
  mmaq(o0, vx[1], p2, p3); mmaq(o2, vx[3], p2, p3);
  mma1688(o1, vm.x, vm.y, p4); mma1688(o3, vm.z, vm.w, p4);
  asm volatile("stmatrix.sync.aligned.m8n8.x4.shared.b16 [%0], {%1,%2,%3,%4};" :: "r"(sl + SM_O + x * 512),
    "r"(pack2(o0[0] + o1[0], o0[1] + o1[1])), "r"(pack2(o0[2] + o1[2], o0[3] + o1[3])),
    "r"(pack2(o2[0] + o3[0], o2[1] + o3[1])), "r"(pack2(o2[2] + o3[2], o2[3] + o3[3])) : "memory");
  if (P) PROF(13);
  bar_arrive(BAR_O, NTHREADS);
  if (x != 3) bar_arrive(BAR_KVF, 128);
  if (EXTRA) {
#pragma unroll
    for (int u = WXE; u < 8; u++) ldsm4t(WX[u], wa + u * 2048);
    bar_sync(BAR_AB2, 128);
  } else {
    bar_arrive(BAR_AB2, 128);
    if (x == 3) {
      float l = ((y[0] + y[1]) + (y[2] + y[3])) + ((y[4] + y[5]) + (y[6] + y[7])) + (y[8] + y[9]);
      l += __shfl_xor_sync(0xffffffffu, l, 1);
      l += __shfl_xor_sync(0xffffffffu, l, 2);
      float inv; asm("rcp.approx.ftz.f32 %0, %1;" : "=f"(inv) : "f"(l));
      if ((lane & 3) == 0) sts32(sb + SM_INV + lane, __float_as_uint(inv));
      __syncwarp();
      mbar_arrive_if(bar + B_L, lane == 0 && s >= 0);
      bar_sync(BAR_KVF, 128);
    }
  }
  if (!EXTRA) { if (a == 0 && s >= 0) vm_ptr[(size_t)s * 128] = vm; } else vm_out = vm;
}

__device__ __forceinline__ void reduce_exchange(int x, int gi, int a, int s, uint32_t sb, uint32_t bar, int lane_in, uint32_t t0, int P, int bid) {
  const int lane = opaque(lane_in);
  const int tt = x * 32 + lane;
  const bool act = tt < 72;
  const int hc = lane & 1;
  const uint32_t rs_addr = sb + SM_RS + tt * 8;
  const uint32_t mem_addr = sb + SM_MEM + (x < 2 ? (tt >> 1) * 16 : 8 * 512 + (4 * gi + (lane >> 1)) * 16);
  const uint32_t mem_step = x < 2 ? 512 : 0;
  const uint32_t ma = mem_addr + (1 + hc) * mem_step;
  const uint32_t r0 = 2 * ((gi - 1 - hc) & 7) + a, r1 = 2 * ((gi - 3 - hc) & 7) + a, r2 = 2 * ((gi - 5 - hc) & 7) + a, r3 = 2 * ((gi - 7) & 7) + a;
  const uint32_t d0 = mapa(ma, r0), e0 = mapa(bar + B_AG + (x < 2 ? 8 : 32), r0);
  const uint32_t d1 = mapa(ma + 2 * mem_step, r1), e1_ = mapa(bar + B_AG + (x < 2 ? 16 : 32), r1);
  const uint32_t d2 = mapa(ma + 4 * mem_step, r2), e2_ = mapa(bar + B_AG + (x < 2 ? 24 : 32), r2);
  const uint32_t d3 = mapa(ma + 6 * mem_step, r3), e3_ = mapa(bar + B_AG + 32, r3);
  char* const xb = reinterpret_cast<char*>((reinterpret_cast<uintptr_t>(g_xch) + 8191) & ~(uintptr_t)8191) + (tt * 16 + (s & 1) * 2048);
  void* const xw = xb + (size_t)bid * 8192;
  const void* const xr1 = xb + (size_t)(bid ^ 16) * 8192;
  const void* const xr2 = xb + (size_t)(bid ^ 32) * 8192;
  const void* const xr3 = xb + (size_t)(bid ^ 48) * 8192;
  const uint32_t tag = (s + 1) & 15;
  mbar_wait(bar + B_RS, s & 1, t0);
  if (P) PROF(20);
  uint32_t w0 = 0, w1 = 0;
  if (act) {
    uint2 r[8];
#pragma unroll
    for (int u = 0; u < 8; u++) r[u] = lds64(rs_addr + u * 576);
    float f0 = ((bflo(r[0].x) + bflo(r[1].x)) + (bflo(r[2].x) + bflo(r[3].x))) + ((bflo(r[4].x) + bflo(r[5].x)) + (bflo(r[6].x) + bflo(r[7].x)));
    float f1 = ((bfhi(r[0].x) + bfhi(r[1].x)) + (bfhi(r[2].x) + bfhi(r[3].x))) + ((bfhi(r[4].x) + bfhi(r[5].x)) + (bfhi(r[6].x) + bfhi(r[7].x)));
    float f2 = ((bflo(r[0].y) + bflo(r[1].y)) + (bflo(r[2].y) + bflo(r[3].y))) + ((bflo(r[4].y) + bflo(r[5].y)) + (bflo(r[6].y) + bflo(r[7].y)));
    float f3 = ((bfhi(r[0].y) + bfhi(r[1].y)) + (bfhi(r[2].y) + bfhi(r[3].y))) + ((bfhi(r[4].y) + bfhi(r[5].y)) + (bfhi(r[6].y) + bfhi(r[7].y)));
    const uint32_t m0 = (__float_as_uint(f0) & ~15u) | tag;
    if (s >= 0) {
      st_b128(xw, m0, __float_as_uint(f1), __float_as_uint(f2), __float_as_uint(f3));
    }
    if (P) PROF(21);
    uint4 e1, e2, e3;
    const uint32_t mb = sb + SM_MB + tt * 16;
    uint32_t tn = clk32() + POLL_DELAY;
    while (true) {
      const uint32_t now = clk32();
      if ((int)(now - tn) >= 0) { cp_async16(mb, xr1); cp_async16(mb + 1152, xr2); cp_async16(mb + 2304, xr3); tn = now + POLL_GAP; }
      e1 = lds128(mb); e2 = lds128(mb + 1152); e3 = lds128(mb + 2304);
      if ((((e1.x ^ tag) | (e2.x ^ tag) | (e3.x ^ tag)) & 15u) == 0 || s < 0) break;
      if (now - t0 > TIMEOUT_CLKS) { g_err = 1; break; }
    }
    if (P) PROF(22);
    f0 = (__uint_as_float(m0) + __uint_as_float(e1.x)) + (__uint_as_float(e2.x) + __uint_as_float(e3.x));
    f1 = (f1 + __uint_as_float(e1.y)) + (__uint_as_float(e2.y) + __uint_as_float(e3.y));
    f2 = (f2 + __uint_as_float(e1.z)) + (__uint_as_float(e2.z) + __uint_as_float(e3.z));
    f3 = (f3 + __uint_as_float(e1.w)) + (__uint_as_float(e2.w) + __uint_as_float(e3.w));
    w0 = pack2(f0, f1); w1 = pack2(f2, f3);
    if (s >= 0) sts64(mem_addr + hc * 8, w0, w1);
  }
  __syncwarp();
  const uint32_t n0 = __shfl_xor_sync(0xffffffffu, w0, 1), n1 = __shfl_xor_sync(0xffffffffu, w1, 1);
  mbar_arrive_if(bar + B_AG + (x == 2 ? 32 : 0), lane == 0);
  if (act && s >= 0) {
    const uint32_t y0 = hc ? n0 : w0, y1 = hc ? n1 : w1, y2 = hc ? w0 : n0, y3 = hc ? w1 : n1;
    st_async16(d0, y0, y1, y2, y3, e0);
    st_async16(d1, y0, y1, y2, y3, e1_);
    st_async16(d2, y0, y1, y2, y3, e2_);
    if (!hc) st_async16(d3, y0, y1, y2, y3, e3_);
  }
  __syncwarp();
  if (P) PROF(23);
}

__global__ void __launch_bounds__(NTHREADS, 1)
chain_kernel(const __grid_constant__ Maps maps, const bf16* __restrict__ mem0, const bf16* x_in, const bf16* Wq, const bf16* Wk, const bf16* Wv,
             const bf16* Wo, const bf16* b2, bf16* out, uint32_t zero) {
  extern __shared__ __align__(1024) unsigned char smem_raw[];
  const uint32_t sb = smem_u32(smem_raw);
  const int tid = __shfl_sync(0xffffffffu, (int)threadIdx.x, threadIdx.x & 31);
  const int warp = __shfl_sync(0xffffffffu, tid >> 5, 0), lane = tid & 31;
  const int rank = blockIdx.x & 15;
  const int cl = blockIdx.x >> 4;
  const int bid = cl * 16 + rank;
  const int gi = rank >> 1, a = rank & 1, head = cl * 8 + gi;
  const uint32_t t0 = clk32();
  const uint32_t bar = sb + SM_BAR;
  const uint32_t sl = sb + lane * 16;
  TR_T(trs);
  auto krow = [&](int sp) { const int idx = sp >> 1; const int p = idx < 8 ? ((gi + idx) & 7) : 8; return 288 * a + 32 * p + 16 * (sp & 1); };
  if (tid == 32) atomicAdd(&g_resident, 1u);
  const int ln_r8 = ((bid & 3) * 4 + warp / 3) + (bid >> 2) * 16, ln_w = warp % 3;
  uint4 lnv[6];
  {
    const uint4* src = reinterpret_cast<const uint4*>(x_in + (size_t)(ln_r8 * 8 + (lane >> 2)) * DM) + ln_w * 24 + (lane & 3);
#pragma unroll
    for (int t = 0; t < 6; t++) lnv[t] = __ldg(src + t * 4);
  }
  if (tid >= 96) {
    const int i = tid - 96, idx = i >> 5, t = lane >> 2, j = lane & 3;
    const int p = idx < 8 ? ((gi + idx) & 7) : 8;
    const uint32_t* src = reinterpret_cast<const uint32_t*>(mem0 + t * DM + 288 * a + 32 * p + 2 * j);
    sts128(sb + SM_MEM + i * 16, src[0], src[4], src[8], src[12]);
    if (i < 216) sts128(sb + SM_MB + i * 16, 0, 0, 0, 0);
  }
  PROF0(39);
  if (tid >= 64 && tid < 68) asm volatile("prefetch.tensormap [%0];" :: "l"(&maps.q + (tid - 64)) : "memory");
  if (warp == 0) {
    if (lane == 0) {
      mbar_init(bar + B_AG, 2); mbar_init(bar + B_AG + 8, 1); mbar_init(bar + B_AG + 16, 1); mbar_init(bar + B_AG + 24, 1); mbar_init(bar + B_AG + 32, 2);
      mbar_init(bar + B_XQK, 1); mbar_init(bar + B_XV, 9); mbar_init(bar + B_RS, 2); mbar_init(bar + B_KV, 1); mbar_init(bar + B_L, 1);
      for (int i = 0; i < 5; i++) mbar_init(bar + B_W + i * 8, 1);
      asm volatile("fence.mbarrier_init.release.cluster;" ::: "memory");
      mbar_expect(bar + B_W, 20 * SLOT); mbar_expect(bar + B_W + 8, 16 * SLOT); mbar_expect(bar + B_W + 16, 9 * SLOT);
      mbar_expect(bar + B_W + 24, 5 * 16384); mbar_expect(bar + B_W + 32, 9 * SLOT);
    }
    __syncwarp();
  }
  {
    const int g = lane >> 2, j = lane & 3;
    const uint32_t red = sb + SM_S + (warp / 3) * 256;
    float f[48];
#pragma unroll
    for (int t = 0; t < 6; t++) {
      f[t * 8 + 0] = bflo(lnv[t].x); f[t * 8 + 1] = bfhi(lnv[t].x); f[t * 8 + 2] = bflo(lnv[t].y); f[t * 8 + 3] = bfhi(lnv[t].y);
      f[t * 8 + 4] = bflo(lnv[t].z); f[t * 8 + 5] = bfhi(lnv[t].z); f[t * 8 + 6] = bflo(lnv[t].w); f[t * 8 + 7] = bfhi(lnv[t].w);
    }
    float sum = 0.f;
#pragma unroll
    for (int i = 0; i < 48; i++) sum += f[i];
    sum += __shfl_xor_sync(~0u, sum, 1); sum += __shfl_xor_sync(~0u, sum, 2);
    if (j == 0) sts32(red + g * 16 + ln_w * 4, __float_as_uint(sum));
    PROF0(40);
    __syncthreads();
    uint4 r = lds128(red + g * 16);
    const float mean = (__uint_as_float(r.x) + __uint_as_float(r.y) + __uint_as_float(r.z)) * (1.f / DM);
    float q = 0.f;
#pragma unroll
    for (int i = 0; i < 48; i++) { f[i] -= mean; q = fmaf(f[i], f[i], q); }
    q += __shfl_xor_sync(~0u, q, 1); q += __shfl_xor_sync(~0u, q, 2);
    if (j == 0) sts32(red + 128 + g * 16 + ln_w * 4, __float_as_uint(q));
    __syncthreads();
    r = lds128(red + 128 + g * 16);
    const float rs = rsqrtf((__uint_as_float(r.x) + __uint_as_float(r.y) + __uint_as_float(r.z)) * (1.f / DM) + 1e-5f);
    uint4* dst = g_xnT + ((size_t)(ln_r8 >> 4) * 9 + ln_w * 3) * 1024 + (ln_r8 & 15) * 64 + j * 8 + g;
#pragma unroll
    for (int t = 0; t < 6; t++)
      stg128(dst + (t >> 1) * 1024 + (t & 1) * 32, pack2(f[t * 8] * rs, f[t * 8 + 1] * rs), pack2(f[t * 8 + 2] * rs, f[t * 8 + 3] * rs),
             pack2(f[t * 8 + 4] * rs, f[t * 8 + 5] * rs), pack2(f[t * 8 + 6] * rs, f[t * 8 + 7] * rs));
  }
  PROF0(41);
  __syncthreads();
  if (tid == 352) {
    asm volatile("red.release.gpu.global.add.u32 [%0], 1;" :: "l"(&g_cntX[bid < 4 ? 0 : 32]) : "memory");
  }
  __syncwarp();
  __syncwarp();
  PROF0(42);
  cluster_sync();
  PROF0(43);
  if (warp < 3) {
    if (lane == 0) {
      if (warp != 1) {
        const int m = warp >> 1;
        const CUtensorMap* mp = m ? &maps.q : &maps.k;
        if (m) { const uint32_t tq = clk32(); while (clk32() - tq < QDELAY) __nanosleep(100); }
        for (int u = 0; u < 10; u++) tma3d(sb + SM_WO + (2 * u + 1 - m) * SLOT, mp, krow(NX + u), head * 2, bar + B_W);
        for (int u = 0; u < 8; u++) tma3d(sb + SM_X + (2 * u + 1 - m) * SLOT, mp, krow(u), head * 2, bar + B_W + 8);
      } else {
        for (int u = 0; u < 9; u++) tma3d(sb + SM_V2 + (4 + u) * SLOT, &maps.v, krow(NV2 + u), head * 2, bar + B_W + 16);
        for (int u = 0; u < 4; u++) tma3d(sb + SM_V2 + u * SLOT, &maps.v, krow(u), head * 2, bar + B_W + 32);
      }
    }
    __syncwarp();
  }

  if (warp < 8) {
    asm volatile("setmaxnreg.inc.sync.aligned.u32 %0;" :: "n"(REG_C));
    const int w = warp;
    const uint32_t wl = sb + (w >> 2) * 2048 + frag_off(lane, w & 3);
    const uint32_t wo = sb + SM_WO + (w >> 1) * 16384 + frag_off(lane, (w & 1) * 2);
    uint32_t Pqk[18 - NX][2][4], Pv[NPV][4];
    uint32_t Xqk[NX][2][4];
    const unsigned epoch_c = g_epoch + 1;
#pragma unroll
    for (int u = 0; u < 20; u++) for (int q = 0; q < 4; q++) Pqk[u >> 1][u & 1][q] = 0;
#pragma unroll
    for (int u = 0; u < NPV; u++) for (int q = 0; q < 4; q++) Pv[u][q] = 0;
#pragma unroll
    for (int u = 0; u < 2 * NX; u++) for (int q = 0; q < 4; q++) Xqk[u >> 1][u & 1][q] = 0;
    const uint32_t partner = rank ^ 1;
    const uint32_t pd = __shfl_sync(~0u, mapa(sb, partner) - sb, 0), od = __shfl_sync(~0u, mapa(sb, 2 * w + a) - sb, 0);
    const bool late = STAGGER && w >= 4;
    const uint32_t ag = bar + B_AG + (late ? 8 : 0);

    for (int s = -1; s < NSEG; s++) {
      const uint32_t par = s & 1;
      float q0[4] = {0.f, 0.f, 0.f, 0.f}, k0[4] = {0.f, 0.f, 0.f, 0.f}, q1[4] = {0.f, 0.f, 0.f, 0.f}, k1[4] = {0.f, 0.f, 0.f, 0.f};
      uint4 B[9] = {};
      uint32_t V2[NV2][4];
      auto qk = [&](int idx) {
        const int s0 = 2 * idx, s1 = 2 * idx + 1;
        if (s0 < NX) { mma16816(q0, Xqk[s0][0], B[idx].x, B[idx].y); mma16816(k0, Xqk[s0][1], B[idx].x, B[idx].y); }
        else { mma16816(q0, Pqk[s0 - NX][0], B[idx].x, B[idx].y); mma16816(k0, Pqk[s0 - NX][1], B[idx].x, B[idx].y); }
        if (s1 < NX) { mma16816(q1, Xqk[s1][0], B[idx].z, B[idx].w); mma16816(k1, Xqk[s1][1], B[idx].z, B[idx].w); }
        else { mma16816(q1, Pqk[s1 - NX][0], B[idx].z, B[idx].w); mma16816(k1, Pqk[s1 - NX][1], B[idx].z, B[idx].w); }
      };
      mbar_wait(bar + B_AG, par, t0);
      if (w == 0) { PROF(0); PROFN(24); PROFS(); }
      B[0] = lds128(sl + SM_MEM);
      qk(0);
      ldsm4t(V2[0], wl + SM_V2); ldsm4t(V2[1], wl + SM_V2 + SLOT);
      if (late) mbar_wait(bar + B_AG + 8, par, t0);
      mbar_wait(ag + 8, par, t0);
      if (w == 0) PROF(1);
      B[1] = lds128(sl + SM_MEM + 512); B[2] = lds128(sl + SM_MEM + 1024);
      bool ok = mbar_try(ag + 16, par);
      qk(1);
      if (!ok) mbar_wait(ag + 16, par, t0);
      B[3] = lds128(sl + SM_MEM + 1536); B[4] = lds128(sl + SM_MEM + 2048);
      ok = mbar_try(ag + 24, par);
      qk(2);
      ldsm4t(V2[2], wl + SM_V2 + 2 * SLOT); ldsm4t(V2[3], wl + SM_V2 + 3 * SLOT);
      qk(3);
      if (!ok) mbar_wait(ag + 24, par, t0);
      if (w == 0) PROF(2);
      B[5] = lds128(sl + SM_MEM + 2560); B[6] = lds128(sl + SM_MEM + 3072);
      ok = mbar_try(bar + B_AG + 32, par);
      qk(4);
      ldsm4t(V2[4], wl + SM_V2 + 4 * SLOT); ldsm4t(V2[5], wl + SM_V2 + 5 * SLOT);
      qk(5);
      if (!ok) mbar_wait(bar + B_AG + 32, par, t0);
      if (w == 0) PROF(3);
      B[7] = lds128(sl + SM_MEM + 3584); B[8] = lds128(sl + SM_MEM + 4096);
      qk(6);
      ldsm4t(V2[6], wl + SM_V2 + 6 * SLOT); ldsm4t(V2[7], wl + SM_V2 + 7 * SLOT);
      qk(7);
      if (late) bar_arrive(BAR_AB, 256);
      qk(8);
      const uint32_t pq0 = pack2(q0[0] + q1[0], q0[1] + q1[1]);
      {
        const uint32_t c0 = movmat(pq0), c1 = movmat(pack2(q0[2] + q1[2], q0[3] + q1[3]));
        const uint32_t c2 = movmat(pack2(k0[0] + k1[0], k0[1] + k1[1])), c3 = movmat(pack2(k0[2] + k1[2], k0[3] + k1[3]));
        const bool swp = sl & 128;
        const uint32_t y0 = swp ? c2 : c0, y1 = swp ? c3 : c1, y2 = swp ? c0 : c2, y3 = swp ? c1 : c3;
        if (s >= 0) st_async16(sl + (pd + w * 512 + SM_XQK), y0, y1, y2, y3, bar + pd + B_XQK);
        sts128(sl + (w * 512 + SM_OQK), y0, y1, y2, y3);
        bar_arrive(BAR_OQK, NTHREADS);
      }
      if (w == 0) PROF(4);
      if (w == 4) PROF(14);
      ldsm4t(V2[8], wl + SM_V2 + 8 * SLOT);
      if (STAGGER && !late) bar_sync(BAR_AB, 256);
      const float vz = __uint_as_float(pq0 & zero);
      float v[4][4] = {{vz, 0.f, 0.f, 0.f}, {vz, 0.f, 0.f, 0.f}, {vz, 0.f, 0.f, 0.f}, {vz, 0.f, 0.f, 0.f}};
      uint32_t WO[16][4];
      if (s == 0) mbar_wait(bar + B_W + 24, 0, t0);
#pragma unroll
      for (int idx = 0; idx < 9; idx++) {
        const int s0 = 2 * idx, s1 = 2 * idx + 1;
        if (s0 < NV2) mma16816(v[s0 & 3], V2[s0], B[idx].x, B[idx].y); else mma16816(v[s0 & 3], Pv[s0 - NV2], B[idx].x, B[idx].y);
        if (s1 < NV2) mma16816(v[s1 & 3], V2[s1], B[idx].z, B[idx].w); else mma16816(v[s1 & 3], Pv[s1 - NV2], B[idx].z, B[idx].w);
        if (idx >= 9 - WEARLY) ldsm4t(WO[idx - (9 - WEARLY)], wo + (idx - (9 - WEARLY)) * 2048);
      }
      {
        const uint32_t vo0 = pack2((v[0][0] + v[1][0]) + (v[2][0] + v[3][0]), (v[0][1] + v[1][1]) + (v[2][1] + v[3][1]));
        const uint32_t vo1 = pack2((v[0][2] + v[1][2]) + (v[2][2] + v[3][2]), (v[0][3] + v[1][3]) + (v[2][3] + v[3][3]));
        const uint32_t l8 = (sl - sb) >> 1;
        if (s >= 0) st_async8(l8 + (sb + pd + w * 256 + SM_XV), vo0, vo1, bar + pd + B_XV);
        sts64(l8 + (sb + w * 256 + SM_OV), vo0, vo1);
        __syncwarp();
        mbar_arrive_if(bar + B_XV, sl == sb && s >= 0);
      }
      if (w == 0) PROF(5);
      if (s == NSEG - 1) break;
#pragma unroll
      for (int u = WEARLY; u < 16; u++) ldsm4t(WO[u], dep(u >= 8 ? wo ^ 32 : wo, WO[(u < 16 - WLATE ? u : 16 - WLATE) - 1][0], zero) + (u & 7) * 2048);
      if (w == 0) PROF(6);
      bar_sync(BAR_O, NTHREADS);
      {
        float m0[4] = {0.f, 0.f, 0.f, 0.f}, m1[4] = {0.f, 0.f, 0.f, 0.f}, m2[4] = {0.f, 0.f, 0.f, 0.f}, m3[4] = {0.f, 0.f, 0.f, 0.f};
        uint32_t ob[4][4];
        bool okl = false;
#pragma unroll
        for (int u = 0; u < 4; u++) ldsm4t(ob[u], sl + SM_O + u * 512);
#pragma unroll
        for (int u = 0; u < 3; u++) {
          mma16816(m0, WO[2 * u], ob[u][0], ob[u][1]);     mma16816(m1, WO[8 + 2 * u], ob[u][0], ob[u][1]);
          mma16816(m2, WO[2 * u + 1], ob[u][2], ob[u][3]); mma16816(m3, WO[8 + 2 * u + 1], ob[u][2], ob[u][3]);
          if (u == 1) okl = mbar_try(bar + B_L, par);
        }
        mma16816(m0, WO[6], ob[3][0], ob[3][1]); mma16816(m1, WO[14], ob[3][0], ob[3][1]);
        if (!okl) mbar_wait(bar + B_L, par, t0);
        const uint2 iv = lds64(sb + SM_INV + ((sl >> 1) & 24));
        mma16816(m2, WO[7], ob[3][2], ob[3][3]); mma16816(m3, WO[15], ob[3][2], ob[3][3]);
        const float i0 = __uint_as_float(iv.x), i1 = __uint_as_float(iv.y);
        const uint32_t c0 = movmat(pack2((m0[0] + m2[0]) * i0, (m0[1] + m2[1]) * i1)), c1 = movmat(pack2((m0[2] + m2[2]) * i0, (m0[3] + m2[3]) * i1));
        const uint32_t c2 = movmat(pack2((m1[0] + m3[0]) * i0, (m1[1] + m3[1]) * i1)), c3 = movmat(pack2((m1[2] + m3[2]) * i0, (m1[3] + m3[3]) * i1));
        if (w == gi) {
          sts128(sl + SM_RS + gi * 576, c0, c1, c2, c3);
          __syncwarp();
          mbar_arrive_if(bar + B_RS, sl == sb && s >= 0);
        } else {
          if (s >= 0) st_async16(sl + (od + SM_RS + gi * 576), c0, c1, c2, c3, bar + od + B_RS);
        }
      }
      if (w == 0) PROF(10);
      if (w == 4) PROF(15);
      if (s < 0) {
        if (w == 3) PROF1(44);
        mbar_wait(bar + B_W, 0, t0);
#pragma unroll
        for (int u = 0; u < 20; u++) ldsm4t(Pqk[u >> 1][u & 1], wl + SM_WO + u * SLOT);
        mbar_wait(bar + B_W + 16, 0, t0);
#pragma unroll
        for (int u = 0; u < NPV; u++) ldsm4t(Pv[u], wl + SM_V2 + (4 + u) * SLOT);
        if (w == 3) PROF1(45);
        bar_sync(BAR_C, 256);
        if (w == 0) {
          if (lane < 5) tma3d(sb + SM_V2 + (4 + lane) * SLOT, &maps.v, krow(4 + lane), head * 2, bar + B_W + 32);
          else if (lane < 10) tma2d(sb + SM_WO + (lane - 5) * 16384, &maps.o, 288 * a + 64 * (lane - 5), head * DH, bar + B_W + 24);
          __syncwarp();
        }
        bar_arrive(BAR_ALL, NTHREADS);
        mbar_wait(bar + B_W + 8, 0, t0);
        mbar_wait(bar + B_W + 32, 0, t0);
      }
      uint32_t keep = 0;
#pragma unroll
      for (int u = 0; u < 2 * NX; u++) {
        if (u == 6) mbar_wait(bar + B_RS, par, t0);
        if (u == 7 || u == 15) { float dz[4] = {0.f, 0.f, 0.f, 0.f}; mma16816(dz, Xqk[(u - 1) >> 1][(u - 1) & 1], zero, zero); keep = __float_as_uint(dz[0]); }
        ldsm4t(Xqk[u >> 1][u & 1], (u < 1 ? wl : dep(wl, (u == 7 || u == 15) && KEEPALIVE ? keep : Xqk[(u - 1) >> 1][(u - 1) & 1][0], zero)) + SM_X + u * SLOT);
      }
      if (w == 0) PROF(11);
    }
    __syncwarp();
    cluster_sync();
    if (rank < 2 && TAILW < NRB) {
      const int unit = (cl * 2 + rank) * 8 + w, ln = threadIdx.x & 31;
      int nl = TAILW - 1, nf = TAILW;
      while (nf < NRB) {
        int fin = 0;
        if (nl >= TAILW) {
          if (ln == 0) {
            while (true) {
              const int dl = nl < NRB ? (int)(ld_relaxed(&g_cntP1[nl * PAD]) - epoch_c * 36) : -1000;
              const int df = (int)(ld_relaxed(&g_cntP2[nf * PAD]) - epoch_c * 36);
              if (dl >= -12) break;
              if (df >= -12) { fin = 1; break; }
              if (timed_out(t0)) { fin = nl >= NRB; break; }
              __nanosleep(100);
            }
          }
          fin = __shfl_sync(~0u, fin, 0);
        }
        row_job<1>(fin, (fin ? nf : nl) * 64 + unit, ln, x_in, b2, out, epoch_c, t0, nl >= TAILW);
        if (fin) nf++; else nl++;
        __syncwarp();
      }
    }
  } else {
    asm volatile("setmaxnreg.dec.sync.aligned.u32 %0;" :: "n"(REG_A));
    const int x = warp - 8;
    const int g = lane >> 2, j = lane & 3;
    const uint32_t sa = sb + SM_S + x * 512 + (32 * j + 4 * (g >> 1) + (g & 1)) * 4;
    const uint32_t sq = sl + (lane & 8);
    if (x < 2) {
      bar_arrive(BAR_ALL, NTHREADS);
      for (int s = -1; s < NSEG - 1; s++) {
        const uint32_t par = s & 1;
        uint4 R[8];
        if (s == 0) mbar_wait(bar + B_W + 24, 0, t0);
        mbar_wait(bar + B_KV, par, t0);
#pragma unroll
        for (int u = 0; u < 8; u++) R[u] = lds128(sl + SM_KX + x * 4096 + u * 512);
        float c0[4] = {0.f, 0.f, 0.f, 0.f}, c1[4] = {0.f, 0.f, 0.f, 0.f}, c2[4] = {0.f, 0.f, 0.f, 0.f}, c3[4] = {0.f, 0.f, 0.f, 0.f};
        bar_sync(BAR_OQK, NTHREADS);
        uint2 o[8];
#pragma unroll
        for (int u = 0; u < 8; u++) o[u] = lds64(sq + SM_OQK + u * 512);
        if (x == 0) PROF(16);
        mbar_wait(bar + B_XQK, par, t0);
        if (x == 0) PROF(17);
        {
          uint2 b[8];
#pragma unroll
          for (int u = 0; u < 8; u++) b[u] = lds64(sq + SM_XQK + u * 512);
#pragma unroll
          for (int u = 0; u < 8; u++) { b[u].x = hadd2bf(b[u].x, o[u].x); b[u].y = hadd2bf(b[u].y, o[u].y); }
          mmaq(c0, R[0], b[0].x, b[0].y); mmaq(c1, R[1], b[1].x, b[1].y); mmaq(c2, R[2], b[2].x, b[2].y); mmaq(c3, R[3], b[3].x, b[3].y);
          mmaq(c0, R[4], b[4].x, b[4].y); mmaq(c1, R[5], b[5].x, b[5].y); mmaq(c2, R[6], b[6].x, b[6].y); mmaq(c3, R[7], b[7].x, b[7].y);
        }
        sts32(sa, __float_as_uint((c0[0] + c1[0]) + (c2[0] + c3[0])));
        sts32(sa + 64, __float_as_uint((c0[1] + c1[1]) + (c2[1] + c3[1])));
        sts32(sa + 8, __float_as_uint((c0[2] + c1[2]) + (c2[2] + c3[2])));
        sts32(sa + 72, __float_as_uint((c0[3] + c1[3]) + (c2[3] + c3[3])));
        if (x == 0) PROF(18);
        uint32_t WX[8][4];
        uint4 vmo;
        softmax_pv<true>(s, x, sb, sl, bar, lane, a, head, t0, WX, vmo, x == 0);
        {
          float m0[4] = {0.f, 0.f, 0.f, 0.f}, m1[4] = {0.f, 0.f, 0.f, 0.f}, m2[4] = {0.f, 0.f, 0.f, 0.f}, m3[4] = {0.f, 0.f, 0.f, 0.f};
          uint32_t ob[4][4];
#pragma unroll
          for (int u = 0; u < 4; u++) ldsm4t(ob[u], sl + SM_O + u * 512);
          const int ln = opaque(lane);
          const uint32_t r_rs2 = mapa(sb + SM_RS + gi * 576 + (32 + (ln & 3)) * 16 + x * 8, 2 * (ln >> 2) + a), r_rsb2 = mapa(bar + B_RS, 2 * (ln >> 2) + a);
          mma16816(m0, WX[0], ob[0][0], ob[0][1]); mma16816(m1, WX[1], ob[0][2], ob[0][3]);
          mma16816(m2, WX[2], ob[1][0], ob[1][1]); mma16816(m3, WX[3], ob[1][2], ob[1][3]);
          mma16816(m0, WX[4], ob[2][0], ob[2][1]); mma16816(m1, WX[5], ob[2][2], ob[2][3]);
          mma16816(m2, WX[6], ob[3][0], ob[3][1]); mma16816(m3, WX[7], ob[3][2], ob[3][3]);
          mbar_wait(bar + B_L, par, t0);
          const uint2 iv = lds64(sb + SM_INV + (ln & 3) * 8);
          const float i0 = __uint_as_float(iv.x), i1 = __uint_as_float(iv.y);
          const uint32_t d0 = movmat(pack2(((m0[0] + m1[0]) + (m2[0] + m3[0])) * i0, ((m0[1] + m1[1]) + (m2[1] + m3[1])) * i1));
          const uint32_t d1 = movmat(pack2(((m0[2] + m1[2]) + (m2[2] + m3[2])) * i0, ((m0[3] + m1[3]) + (m2[3] + m3[3])) * i1));
          if (s >= 0) st_async8(r_rs2, d0, d1, r_rsb2);
          if (a == 0 && s >= 0) g_Vmf[((size_t)head * NSEG + s) * 128 + x * 32 + ln] = vmo;
        }
        if (x == 0) PROF(19);
        reduce_exchange(x, gi, a, s, sb, bar, lane, t0, x == 0, bid);
      }
      bar_sync(BAR_OQK, NTHREADS);
    } else {
      const unsigned epoch = g_epoch + 1;
      const uint4* kx_g = g_Kf + (size_t)head * 128 * 256;
      const uint4* vx_g = g_Vf + (size_t)head * NSEG * 512;
      const int hh = x - 2;
      const uint32_t sm_ = sa - hh * 512 + hh * 8;
      uint4* const km_ptr = g_Kmf + (size_t)head * NSEG * 128 + hh * 64 + lane;
      if (x == 2) bar_arrive(BAR_ALL, NTHREADS);
      for (int s = -1; s < NSEG; s++) {
        const uint32_t par = s & 1;
        uint2 Q[4], K[4], oq[4], okk[4];
        if (s < NSEG - 1) mbar_wait(bar + B_KV, par, t0);
        bar_sync(BAR_OQK, NTHREADS);
#pragma unroll
        for (int u = 0; u < 4; u++) { Q[u] = lds64(sq + SM_OQK + (hh * 4 + u) * 512); K[u] = lds64((sq ^ 8) + SM_OQK + (hh * 4 + u) * 512); }
        mbar_wait(bar + B_XQK, par, t0);
        float c0[4] = {0.f, 0.f, 0.f, 0.f}, c1[4] = {0.f, 0.f, 0.f, 0.f}, c2[4] = {0.f, 0.f, 0.f, 0.f}, c3[4] = {0.f, 0.f, 0.f, 0.f};
#pragma unroll
        for (int u = 0; u < 4; u++) { oq[u] = lds64(sq + SM_XQK + (hh * 4 + u) * 512); okk[u] = lds64((sq ^ 8) + SM_XQK + (hh * 4 + u) * 512); }
#pragma unroll
        for (int u = 0; u < 4; u++) {
          Q[u].x = hadd2bf(Q[u].x, oq[u].x); Q[u].y = hadd2bf(Q[u].y, oq[u].y); K[u].x = hadd2bf(K[u].x, okk[u].x); K[u].y = hadd2bf(K[u].y, okk[u].y);
        }
#pragma unroll
        for (int u = 0; u < 4; u += 2) {
          mma1688(c0, K[u].x, K[u].y, Q[u].x);
          mma1688(c1, K[u].x, K[u].y, Q[u].y);
          mma1688(c2, K[u + 1].x, K[u + 1].y, Q[u + 1].x);
          mma1688(c3, K[u + 1].x, K[u + 1].y, Q[u + 1].y);
        }
        sts32(sm_, __float_as_uint((c0[0] + c1[2]) + (c2[0] + c3[2])));
        sts32(sm_ + 64, __float_as_uint((c0[1] + c1[3]) + (c2[1] + c3[3])));
        uint32_t dummy[8][4]; uint4 dummy4;
        if (s < NSEG - 1) softmax_pv<false>(s, x, sb, sl, bar, lane, a, head, t0, dummy, dummy4, 0);
        if (a == 0 && s >= 0) {
          km_ptr[(size_t)s * 128] = make_uint4(K[0].x, K[0].y, K[1].x, K[1].y);
          km_ptr[(size_t)s * 128 + 32] = make_uint4(K[2].x, K[2].y, K[3].x, K[3].y);
        }
        if (s == NSEG - 1) break;
        if (x == 2) {
          reduce_exchange(x, gi, a, s, sb, bar, lane, t0, 0, bid);
          if (lane == 0) mbar_expect(bar + B_RS, RS_BYTES);
        } else {
          if (lane == 0 && s >= 0 && s + 1 < NSEG - 1) {
            mbar_expect(bar + B_KV, 16384);
            bulk_g2s(sb + SM_KX, kx_g + (size_t)(s + 1) * 512, 8192, bar + B_KV);
            bulk_g2s(sb + SM_VX, vx_g + (size_t)(s + 1) * 512, 8192, bar + B_KV);
          }
          __syncwarp();
          mbar_wait(bar + B_RS, par, t0);
          if (lane == 0) {
            const int nb = s < 0 ? 0 : 1024;
            mbar_expect(bar + B_AG + 8, nb); mbar_expect(bar + B_AG + 16, nb); mbar_expect(bar + B_AG + 24, nb); mbar_expect(bar + B_AG + 32, s < 0 ? 0 : 960);
            mbar_expect(bar + B_XQK, 4096); mbar_expect(bar + B_XV, 2048);
            if (a == 0 && (s & 3) == 0 && s > 0) { st_release(&g_memflag[head * 8], epoch * 64 + s); if (bid == 0) TR_LOG(9 | (((s - 1) >> 2) << 24), trs, trs); }
            if ((s & 3) == 2 && s + 2 < NSEG) {
              while (ld_acquire(&g_kvflag[((s + 2) >> 2) * 64 + head]) != epoch) { if (timed_out(t0)) break; }
              while (ld_acquire(&g_kvflag[((s + 2) >> 2) * 64 + 32 + head]) != epoch) { if (timed_out(t0)) break; }
              asm volatile("fence.proxy.async.global;" ::: "memory");
              asm volatile("cp.async.bulk.prefetch.L2.global [%0], 32768;" :: "l"(kx_g + (size_t)(s + 2) * 512) : "memory");
              asm volatile("cp.async.bulk.prefetch.L2.global [%0], 32768;" :: "l"(vx_g + (size_t)(s + 2) * 512) : "memory");
            }
          }
          __syncwarp();
          if (s >= 0) {
            float dz[4] = {0.f, 0.f, 0.f, 0.f};
            while (true) {
              mma16816(dz, zero, zero, zero, zero, zero, zero);
              if (__all_sync(~0u, mbar_test(bar + B_AG + __float_as_uint(dz[0]), par ^ 1) || timed_out(t0))) break;
              __nanosleep(KEEPALIVE);
            }
          }
          if (s < 0) {
            __syncwarp();
            bar_sync(BAR_ALL, NTHREADS);
            if (lane == 0) {
              while (ld_acquire(&g_kvflag[head]) != epoch) { if (timed_out(t0)) break; __nanosleep(100); }
              while (ld_acquire(&g_kvflag[32 + head]) != epoch) { if (timed_out(t0)) break; __nanosleep(100); }
              asm volatile("fence.proxy.async.global;" ::: "memory");
              mbar_expect(bar + B_KV, 16384);
              bulk_g2s(sb + SM_KX, kx_g, 8192, bar + B_KV);
              bulk_g2s(sb + SM_VX, vx_g, 8192, bar + B_KV);
            }
          }
        }
        __syncwarp();
      }
    }
    {
      mbar_wait(bar + B_XV, (NSEG - 1) & 1, t0);
      const uint32_t lv = sb + x * 512 + lane * 8;
      const uint2 ov0 = lds64(lv + SM_OV), xv0 = lds64(lv + SM_XV), ov1 = lds64(lv + SM_OV + 256), xv1 = lds64(lv + SM_XV + 256);
      if (a == 0) g_Vmf[((size_t)head * NSEG + NSEG - 1) * 128 + x * 32 + lane] = make_uint4(hadd2bf(ov0.x, xv0.x), hadd2bf(ov0.y, xv0.y), hadd2bf(ov1.x, xv1.x), hadd2bf(ov1.y, xv1.y));
      bar_sync(BAR_S, 128);
      if (x == 3 && a == 0 && lane == 0) { st_release(&g_memflag[head * 8], (g_epoch + 1) * 64 + 64); if (bid == 0) TR_LOG(9 | (15 << 24), trs, trs); }
    }
    __syncwarp();
    cluster_sync();
  }
}
}
__global__ void gate_kernel() {
  const uint32_t t0 = clk32();
  const unsigned need = (g_epoch + 1) * 64u;
  while ((int)(ld_relaxed(&g_resident) - need) < 0) { if (timed_out(t0)) break; }
}
namespace mega {
constexpr int NS = 5;
constexpr int SM_B = 0, SM_A = 9 * 16384, SM_BAR = SM_A + NS * 16384;
constexpr int B_FA = 0, B_EA = NS * 8, B_FB = 2 * NS * 8, B_EB = B_FB + 96, B_D = B_EB + 24, B_TK = B_D + 32, B_QF = B_TK + 32, B_QE = B_QF + 16,
              B_PD = B_QE + 16, B_PE = B_PD + 16, B_BF = B_PE + 16, B_BE = B_BF + 8;
constexpr int SM_DESC = SM_BAR + 512;
constexpr int SM_TQ = SM_DESC + 64;
constexpr int SM_TK = SM_TQ + 32;
constexpr int SM_PUB = SM_TK + 16;
constexpr int SM_RED = SM_PUB + 16;
constexpr int SM_TOTAL = SM_RED + 256;
enum { T_K = 0, T_V = 1, T_QA = 2, T_OP = 3, T_F1 = 4, T_F2 = 5, T_END = 6 };
constexpr int NORDER = 468;
__constant__ unsigned short c_order[NORDER] = {
  1408,3456,5504,7552,9600,11648,13696,15744,17792,19840,21888,23936,25984,28032,30080,32128,34176,36224,38272,40320,
  42368,44416,46464,48512,50560,52608,54656,56704,58752,60800,62848,64896,728,2776,4824,6872,8920,10968,13016,15064,
  17112,19160,21208,23256,25304,27352,29400,31448,514,2562,4610,6658,8706,10754,12802,14850,16898,18946,20994,23042,
  25090,27138,29186,31234,515,2563,4611,6659,8707,10755,12803,14851,16899,18947,20995,23043,25091,27139,29187,31235,
  33283,35331,516,2564,4612,6660,8708,10756,12804,14852,16900,33496,35544,37592,39640,41688,43736,45784,47832,49880,
  51928,53976,56024,58072,60120,62168,64216,546,2594,4642,6690,8738,10786,12834,14882,16930,18978,21026,23074,25122,
  27170,29218,31266,18948,20996,23044,25092,27140,29188,31236,33284,35332,547,2595,4643,6691,8739,10787,12835,14883,
  16931,18979,21027,23075,25123,27171,29219,31267,33315,35363,450,2498,4546,6594,8642,10690,12738,14786,16834,18882,
  20930,22978,25026,27074,29122,31170,517,2565,4613,6661,8709,10757,12805,14853,16901,18949,20997,23045,25093,27141,
  29189,31237,33285,35333,548,2596,4644,6692,8740,10788,12836,14884,16932,18980,21028,23076,25124,27172,29220,31268,
  33316,35364,451,2499,4547,6595,8643,10691,12739,14787,16835,18883,20931,22979,25027,27075,29123,31171,33219,35267,
  549,2597,4645,6693,8741,10789,12837,14885,16933,474,2522,4570,6618,8666,10714,12762,14810,18981,21029,23077,
  25125,27173,29221,31269,33317,35365,16858,18906,20954,23002,25050,27098,29146,31194,452,2500,4548,6596,8644,10692,
  12740,14788,16836,475,2523,4571,6619,8667,10715,12763,14811,16859,18907,20955,23003,25051,27099,29147,31195,33243,
  35291,370,2418,4466,6514,8562,10610,12658,14706,16754,18802,20850,22898,24946,26994,29042,31090,18884,20932,22980,
  25028,27076,29124,31172,33220,35268,243,2291,4339,6387,8435,10483,12531,14579,16627,18675,20723,22771,24819,26867,
  28915,30963,33011,35059,251,2299,4347,6395,8443,10491,12539,14587,16635,453,2501,4549,6597,8645,10693,12741,
  14789,16837,18885,20933,22981,25029,27077,29125,31173,33221,35269,18683,20731,22779,24827,26875,28923,30971,33019,35067,
  476,2524,4572,6620,8668,10716,12764,14812,16860,18908,20956,23004,25052,27100,29148,31196,33244,35292,244,2292,
  4340,6388,8436,10484,12532,14580,16628,18676,20724,22772,24820,26868,28916,30964,33012,35060,477,2525,4573,6621,
  8669,10717,12765,14813,16861,18909,20957,23005,25053,27101,29149,31197,33245,35293,245,2293,4341,6389,8437,10485,
  12533,14581,16629,252,2300,4348,6396,8444,10492,12540,14588,16636,18684,20732,22780,24828,26876,28924,30972,33020,
  35068,18677,20725,22773,24821,26869,28917,30965,33013,35061,253,2301,4349,6397,8445,10493,12541,14589,16637,18685,
  20733,22781,24829,26877,28925,30973,33021,35069,
};
constexpr int NTASK = NORDER;
constexpr int NWTASK = 2048;
#define HOLD 0
#define RELKS 0
#define TSTKS 2
#define MREG 192
#define EARLYHO 1
#define HINT 15
#define URGENT 14
#define F1SPLIT 1
#define PFA 0
#define PFB 0
#define LATECLAIM 260
#define LATETH 1
#define PRE 2
constexpr int REG_C = MREG, REG_P = 504 - 2 * MREG;
static_assert(2 * REG_C + REG_P <= 504, "register pool");

__device__ unsigned g_ticket, g_wticket;

template <int B> struct IntC { static constexpr int value = B; };
__device__ __forceinline__ void red_release(unsigned* p) { asm volatile("red.release.gpu.global.add.u32 [%0], 1;" :: "l"(p) : "memory"); }
__device__ __forceinline__ void wait_cnt(const unsigned* p, unsigned need, int far, uint32_t t0) {
  while (true) {
    const int d = (int)(ld_relaxed(p) - need);
    if (d >= 0) break;
    if (timed_out(t0)) break;
    __nanosleep(d <= -far ? 1000 : 40);
  }
  (void)ld_acquire(p);
}
__device__ __forceinline__ float gelu_tanh(float z) {
  const float u = z * fmaf(z * z, 0.044715f * 0.7978845608028654f, 0.7978845608028654f);
  float t; asm("tanh.approx.f32 %0, %1;" : "=f"(t) : "f"(u));
  return fmaf(z, t, z);
}

__device__ __forceinline__ void arrive2_if(uint32_t local, uint32_t pd, int p, int cnt) {
  asm volatile("{ .reg .pred q; setp.ne.b32 q, %2, 0; @q mbarrier.arrive.shared::cta.b64 _, [%0], %3; @q mbarrier.arrive.shared::cluster.b64 _, [%1], %3; }"
    :: "r"(local), "r"(local + pd), "r"(p), "r"(cnt) : "memory");
}
__device__ __forceinline__ void bulk_mc(uint32_t dst, const void* src, uint32_t bytes, uint32_t bar) {
  asm volatile("cp.async.bulk.shared::cluster.global.mbarrier::complete_tx::bytes.multicast::cluster [%0], [%1], %2, [%3], %4;"
    :: "r"(dst), "l"(src), "r"(bytes), "r"(bar), "h"((uint16_t)3) : "memory");
}
__device__ __forceinline__ void bulk_mc_h(uint32_t dst, const void* src, uint32_t bytes, uint32_t bar, uint64_t pol) {
  asm volatile("cp.async.bulk.shared::cluster.global.mbarrier::complete_tx::bytes.multicast::cluster.L2::cache_hint [%0], [%1], %2, [%3], %4, %5;"
    :: "r"(dst), "l"(src), "r"(bytes), "r"(bar), "h"((uint16_t)3), "l"(pol) : "memory");
}
__device__ __forceinline__ int op_kb0(int kc) { return kc < 2 ? 12 * kc : 4 + 10 * kc; }
__device__ __forceinline__ int task_nkb(int type, int kc) { return type == T_OP ? (kc < 2 ? 12 : 10) : type == T_F2 ? 12 : 9; }

__device__ __forceinline__ void finish(unsigned epoch) {
  if (atomicAdd(&g_done, 1u) == epoch * 3 * gridDim.x - 1) { g_ticket = 0; g_wticket = 0; g_epoch = epoch; }
}
struct Maps { CUtensorMap m[6]; };
struct WPtr { const char* p[6]; };

__global__ void __launch_bounds__(384, 1)
mega_kernel(const __grid_constant__ Maps maps, const bf16* __restrict__ x, const bf16* __restrict__ b1, const bf16* __restrict__ b2,
            bf16* __restrict__ out, const __grid_constant__ WPtr wp) {
  extern __shared__ __align__(1024) unsigned char smem_raw[];
  const uint32_t sb = smem_u32(smem_raw);
  const int tid = threadIdx.x, wg = __shfl_sync(~0u, tid >> 7, 0), lane = tid & 31, w = __shfl_sync(~0u, (tid >> 5) & 3, 0);
  const uint32_t bar = sb + SM_BAR;
  const uint32_t t0 = clk32();
  unsigned first = 0;
  if (tid == 288) { if (!(blockIdx.x & 1)) first = atomicAdd(&g_ticket, 1u); first += c_order[blockIdx.x & 31] >> 30; }
  if (tid == 256) asm volatile("prefetch.tensormap [%0];" :: "l"(&maps.m[blockIdx.x & 1]) : "memory");
  if (tid == 0) {
    for (int i = 0; i < NS; i++) { mbar_init(bar + B_FA + i * 8, 1); mbar_init(bar + B_EA + i * 8, 8); }
    for (int i = 0; i < 3; i++) mbar_init(bar + B_FB + i * 8, 1);
    for (int i = 0; i < 3; i++) mbar_init(bar + B_EB + i * 8, 4);
    for (int i = 0; i < 4; i++) mbar_init(bar + B_D + i * 8, 1);
    for (int i = 0; i < 4; i++) mbar_init(bar + B_TK + i * 8, 1);
    for (int i = 0; i < 2; i++) { mbar_init(bar + B_QF + i * 8, 1); mbar_init(bar + B_QE + i * 8, 1); mbar_init(bar + B_PD + i * 8, 4); mbar_init(bar + B_PE + i * 8, 1); }
    mbar_init(bar + B_BF, 1); mbar_init(bar + B_BE, 1);
    asm volatile("fence.mbarrier_init.release.cluster;" ::: "memory");
  }
  const int rank = blockIdx.x & 1;
  const uint32_t pd = __shfl_sync(~0u, mapa(sb, rank ^ 1) - sb, 0);
  const unsigned ep0 = *(volatile unsigned*)&g_epoch;
  const unsigned epoch = ep0 + 1;
  __syncthreads();
  asm volatile("barrier.cluster.arrive.relaxed.aligned; barrier.cluster.wait.aligned;" ::: "memory");
  if (wg == 2) {
    asm volatile("setmaxnreg.dec.sync.aligned.u32 %0;" :: "n"(REG_P));
    if (w == 0) {
      {
        int st = 0, ph = 1, seq = 0, qi = 0;
        uint32_t bjob = 0, ebph = 1; int th = 3, bj = 0;
        bool hold = true;
        auto bservice = [&]() {
          if (th == 3) {
            if (!mbar_test(bar + B_BF, bj & 1)) return;
            asm volatile("ld.shared.b32 %0, [%1];" : "=r"(bjob) : "r"(sb + SM_RED) : "memory");
            bjob = __shfl_sync(~0u, bjob, 0);
            th = 0; bj++;
          }
          if (hold && th == 1 && clk32() - t0 < HOLD) return;
          if (!mbar_test(bar + B_EB + th * 8, ebph)) return;
          const int type = bjob & 255, sl = (bjob >> 8) & 255, kc = (bjob >> 16) & 255;
          const CUtensorMap* mp = &maps.m[type];
          const uint32_t fb = bar + B_FB + th * 8, dst = sb + SM_B + th * 49152;
          if (elect()) {
            mbar_expect(fb, 49152);
            if (type <= T_QA) tma3d(dst, mp, th * 192, sl * 2, fb);
            else if (type == T_F1) { tma5d(dst, mp, sl * 128, th * 6, fb); tma5d(dst + 24576, mp, sl * 128 + 64, th * 6, fb); }
            else {
              const int u0 = (type == T_OP ? op_kb0(kc) : kc * 12) * 2 + th * 8;
              tma5d(dst, mp, sl * 96, u0, fb); tma5d(dst + 16384, mp, sl * 96 + 32, u0, fb); tma5d(dst + 32768, mp, sl * 96 + 64, u0, fb);
            }
            if (th == 2) mbar_arrive(bar + B_BE);
          }
          if (++th == 3) ebph ^= 1;
        };
        auto pwait = [&](uint32_t b, uint32_t par) {
          while (!mbar_test(b, par)) { bservice(); if (timed_out(t0)) break; }
        };
        auto pop = [&]() {
          pwait(bar + B_QF + (qi & 1) * 8, (qi >> 1) & 1);
          uint2 e = lds64(sb + SM_TQ + (qi & 1) * 16);
          e.x = __shfl_sync(~0u, e.x, 0); e.y = __shfl_sync(~0u, e.y, 0);
          if (elect()) mbar_arrive(bar + B_QE + (qi & 1) * 8);
          qi++;
          return e;
        };
        while (true) {
          const uint2 e = pop();
          const int type = e.x & 255;
          if (type == T_END) break;
          const int sl = (e.x >> 8) & 255, kc = (e.x >> 16) & 255, rb = e.x >> 24;
          if (elect()) {
            sts64(sb + SM_DESC + (seq & 3) * 16, e.x, e.y | st | (ph << 8));
            mbar_arrive(bar + B_D + (seq & 3) * 8);
          }
          seq++;
          const int nkb = task_nkb(type, kc), kb0 = type == T_OP ? op_kb0(kc) : kc * 12;
          const uint4* A = type <= T_QA ? g_xnT : type == T_OP ? g_oT : type == T_F1 ? g_hnT : g_gT;
          const int ktot = type == T_OP ? 64 : type == T_F2 ? 72 : 9;
          const uint4* src = A + ((size_t)rb * ktot + kb0) * 1024 + rank * 512;
          bservice();
          for (int kb = 0; kb < nkb; kb++) {
            pwait(bar + B_EA + st * 8, ph);
            if (elect()) {
              mbar_expect(bar + B_FA + st * 8, 16384);
              if ((HINT & 8) && (type & 1) && type > T_QA && sl >= 4) bulk_mc_h(sb + SM_A + st * 16384 + rank * 8192, src, 8192, bar + B_FA + st * 8, pol_first());
              else bulk_mc(sb + SM_A + st * 16384 + rank * 8192, src, 8192, bar + B_FA + st * 8);
            }
            src += 1024;
            if (hold && kb == 2) { hold = false; bservice(); bservice(); }
            if (++st == NS) { st = 0; ph ^= 1; }
          }
          if (type == T_QA) {
            const size_t so = (size_t)sl * NSEG + rb * 4;
            const int mpos = (e.y >> 19) & 1 ? 2 : 4;
            for (int q = 0; q < 5; q++) {
              pwait(bar + B_EA + st * 8, ph);
              const uint32_t fa = bar + B_FA + st * 8, dst = sb + SM_A + st * 16384;
              const uint4* p = q < 2 ? g_Kf + so * 512 + q * 1024 : g_Vf + so * 512 + (q - (mpos == 2 ? 3 : 2)) * 1024;
              if (elect()) {
                mbar_expect(fa, q == 4 && mpos == 4 ? 0 : 16384);
                if (q != mpos) { if (HINT & 2) bulk_g2s_h(dst, p, 16384, fa, pol_first()); else bulk_g2s(dst, p, 16384, fa); }
                else if (q == 2) { bulk_g2s(dst, g_Kmf + so * 128, 8192, fa); bulk_g2s(dst + 8192, g_Vmf + so * 128, 8192, fa); }
              }
              if (++st == NS) { st = 0; ph ^= 1; }
            }
          }
        }
        while (th < 3) { bservice(); if (timed_out(t0)) break; }
        if (elect()) {
          for (int i = 0; i < 2; i++) {
            sts64(sb + SM_DESC + ((seq + i) & 3) * 16, T_END, i);
            mbar_arrive(bar + B_D + ((seq + i) & 3) * 8);
          }
        }
      }
      __syncwarp();
      asm volatile("barrier.cluster.arrive.relaxed.aligned; barrier.cluster.wait.aligned;" ::: "memory");
    } else if (w == 1) {
      if (lane == 0) {
        uint32_t fbph = 0;
        int qi = 0, tk = 0, tiles = 0, pubs = 0, pub0 = 0, pub1 = 0;
        auto service = [&]() {
          bool any = false;
          if (mbar_test(bar + B_PD, pub0 & 1)) {
            const uint2 p = lds64(sb + SM_PUB);
            mbar_arrive(bar + B_PE);
            if (p.x | p.y) red_release(reinterpret_cast<unsigned*>(((unsigned long long)p.y << 32) | p.x));
            pub0++; pubs++; any = true;
          }
          if (mbar_test(bar + B_PD + 8, pub1 & 1)) {
            const uint2 p = lds64(sb + SM_PUB + 8);
            mbar_arrive(bar + B_PE + 8);
            if (p.x | p.y) red_release(reinterpret_cast<unsigned*>(((unsigned long long)p.y << 32) | p.x));
            pub1++; pubs++; any = true;
          }
          return any;
        };
        auto can_post = [&]() { return qi == 0 || mbar_test(bar + B_QE + ((qi - 1) & 1) * 8, ((qi - 1) >> 1) & 1); };
        auto post = [&](uint32_t x, uint32_t y) {
          sts64(sb + SM_TQ + (qi & 1) * 16, x, y);
          mbar_arrive(bar + B_QF + (qi & 1) * 8);
          qi++;
        };
        while (true) {
          unsigned task;
          if (rank == 0) {
            task = tk == 0 ? first : atomicAdd(&g_ticket, 1u);
            asm volatile("st.async.shared::cluster.mbarrier::complete_tx::bytes.b32 [%0], %1, [%2];"
              :: "r"(sb + SM_TK + (tk & 3) * 4 + pd), "r"(task), "r"(bar + B_TK + (tk & 3) * 8 + pd) : "memory");
          } else {
            mbar_expect(bar + B_TK + (tk & 3) * 8, 4);
            while (!mbar_test(bar + B_TK + (tk & 3) * 8, (tk >> 2) & 1)) { service(); if (timed_out(t0)) break; }
            asm volatile("ld.shared.b32 %0, [%1];" : "=r"(task) : "r"(sb + SM_TK + (tk & 3) * 4) : "memory");
          }
          tk++;
          if (task >= (unsigned)NTASK) break;
          int type, sl, kc = 0, rb0, n;
          {
            const int e = c_order[task], r = e >> 11;
            type = e & 7; rb0 = (e >> 3) & 15; n = (e >> 7) & 15;
            if (type == 0) { type = rank; sl = r; }
            else {
              if (type & 1) { kc = r / 3; sl = r % 3; } else sl = r;
              sl = 2 * sl + rank;
            }
          }
          const int nkb = task_nkb(type, kc);
          auto deps_ready = [&](int rb, bool mem) -> bool {
            if (mem) return (int)(ld_acquire(&g_memflag[sl * 8]) - (epoch * 64 + rb * 4 + 4)) >= 0;
            if (type == T_QA) return ld_acquire(&g_kvflag[rb * 64 + sl]) == epoch && ld_acquire(&g_kvflag[rb * 64 + 32 + sl]) == epoch;
            if (type == T_OP) return (int)(ld_acquire(&g_cntO[(rb * 8 + kc) * PAD]) - epoch * (nkb >> 1)) >= 0;
            if (type == T_F1) return (int)(ld_acquire(&g_cntH[rb * PAD]) - epoch * 64) >= 0;
            if (type == T_F2) return (int)(ld_acquire(&g_cntG[(rb * 8 + kc) * PAD]) - epoch * 6) >= 0;
            return rb >= rb0 + 2 || (rb == 0 ? (int)(ld_acquire(&g_cntX[0]) - epoch * 4) >= 0 : (int)(ld_acquire(&g_cntX[32]) - epoch * 60) >= 0);
          };
          int t = 0;
          bool bpost = false;
          bool mem = false, rdy = false, mnow = false;
          while (t < n) {
            bool prog = false;
            if (!bpost && (tk == 1 || mbar_test(bar + B_BE, tk & 1))) {
              sts32(sb + SM_RED, type | (sl << 8) | (kc << 16));
              mbar_arrive(bar + B_BF);
              bpost = true; prog = true;
            }
            prog |= service();
            {
              const int rb = rb0 + t;
              if (!rdy && deps_ready(rb, mem)) {
                rdy = true;
                mnow = type == T_QA && !mem && deps_ready(rb, true);
                if (!mem && (type > T_V || t < 2)) asm volatile("fence.proxy.async.global;" ::: "memory");
              }
              if (rdy && mem) { rdy = false; mem = false; t++; prog = true; }
              else if (rdy && bpost && can_post()) {
                post(type | (sl << 8) | (kc << 16) | (rb << 24), ((t == n - 1) << 16) | ((t < 2) << 17) | (fbph << 18) | (mnow << 19));
                rdy = false; prog = true;
                if (!mem) tiles++;
                if (type == T_QA && !mem && !mnow) mem = true; else { mem = false; t++; }
              }
            }
            if (!prog) { if (timed_out(t0)) break; __nanosleep(rdy ? 20 : 80); }
          }
          fbph ^= 1;
          if (rb0 + n > URGENT && type >= T_QA) while (pubs < tiles) { if (!service()) __nanosleep(20); if (timed_out(t0)) break; }
        }
        while (!can_post()) { service(); if (timed_out(t0)) break; }
        post(T_END, 0);
        while (pubs < tiles) { if (!service()) { if (timed_out(t0)) break; __nanosleep(20); } }
        finish(epoch);
      }
      __syncwarp();
      asm volatile("barrier.cluster.arrive.relaxed.aligned; barrier.cluster.wait.aligned;" ::: "memory");
    } else {
      int id = 0;
      if (lane == 0) id = (int)atomicAdd(&g_wticket, 1u);
      id = __shfl_sync(~0u, id, 0);
      int nl = id < 128 ? (id & 1) : TAILW, nf = id < 128 ? ((id & 1) ^ 1) : TAILW;
      while (nl < TAILW || nf < TAILW) {
        int fin = 0;
        if (lane == 0) {
          while (true) {
            const int dl = nl < TAILW ? (int)(ld_relaxed(&g_cntP1[nl * PAD]) - epoch * 36) : -1000;
            const int df = nf < TAILW ? (int)(ld_relaxed(&g_cntP2[nf * PAD]) - epoch * 36) : -1000;
            if (dl >= -PRE) break;
            if (df >= -PRE) { fin = 1; break; }
            if (timed_out(t0)) { fin = nl >= TAILW; break; }
            __nanosleep(dl <= -36 && df <= -36 ? 500 : 100);
          }
        }
        fin = __shfl_sync(~0u, fin, 0);
        const int rb = fin ? nf : nl;
        if (fin) nf += 2; else nl += 2;
        row_job<2>(fin, rb * 64 + (id >> 1), lane, x, b2, out, epoch, t0, true);
        __syncwarp();
      }
      if (lane == 0) finish(epoch);
      __syncwarp();
      asm volatile("barrier.cluster.arrive.relaxed.aligned; barrier.cluster.wait.aligned;" ::: "memory");
    }
  } else {
    asm volatile("setmaxnreg.inc.sync.aligned.u32 %0;" :: "n"(REG_C));
    const int g = lane >> 2, j = lane & 3;
    const int l0 = __shfl_sync(~0u, lane == 0, lane);
    for (int seq = wg;; seq += 2) {
      mbar_wait(bar + B_D + (seq & 3) * 8, (seq >> 2) & 1, t0);
      uint2 d = lds64(sb + SM_DESC + (seq & 3) * 16);
      d.x = __shfl_sync(~0u, d.x, 0); d.y = __shfl_sync(~0u, d.y, 0);
      const int type = d.x & 255;
      const int sl = (d.x >> 8) & 255, kc = (d.x >> 16) & 255, rb = d.x >> 24;
      const int nkb = task_nkb(type, kc);
      const int last = (d.y >> 16) & 1; const bool needb = (d.y >> 17) & 1;
      int st = d.y & 255, ph = ((d.y >> 8) & 1) ^ 1, prev = 0;
      float acc[2][64];
      {
        const uint32_t* bp = reinterpret_cast<const uint32_t*>(b1 + sl * 128) + j;
#pragma unroll
        for (int i = 0; i < 16; i++) {
          uint32_t b = 0;
          if (type == T_F1) b = ldg32(bp + i * 4);
          acc[0][4 * i] = acc[0][4 * i + 2] = acc[1][4 * i] = acc[1][4 * i + 2] = bflo(b);
          acc[0][4 * i + 1] = acc[0][4 * i + 3] = acc[1][4 * i + 1] = acc[1][4 * i + 3] = bfhi(b);
        }
      }
      fence_regs(acc[0]); fence_regs(acc[1]);
      if (seq > 0) bar_sync(3 + wg, 256);
      if (type == T_END) { if (d.y == 0) bar_arrive(3 + (wg ^ 1), 256); break; }
      TR_T(tr0);
      auto mainloop = [&](auto mode) {
        constexpr int MD = decltype(mode)::value;
        constexpr int PER = MD == 2 ? 4 : 3;
        const uint64_t a_hi = make_desc(0, 128, type == T_QA ? 2048 : 1024, 0), b_hi = MD == 2 ? make_desc(0, 16384, 512, 2) : make_desc(0, 24576, 1024, 1);
        const uint32_t a_off = type == T_QA ? 64 : 512;
        bool oka = false;
        int eb = 0, ec = 0;
        int bt = 0, bk = 0;
        for (int kb = 0; kb < nkb; kb++) {
          if (needb && bk == 0) mbar_wait(bar + B_FB + bt * 8, (d.y >> 18) & 1, t0);
          if (!oka) mbar_wait(bar + B_FA + st * 8, ph, t0);
          const uint64_t da = a_hi + ((((sb + SM_A) & 0x3FFFF) >> 4) + st * 1024), db = b_hi + ((((sb + SM_B) & 0x3FFFF) >> 4) + bt * 3072 + bk * (MD == 2 ? 256 : 512));
          if (++bk == PER) { bk = 0; bt++; }
          int nst = st + 1, nph = ph;
          if (nst == NS) { nst = 0; nph ^= 1; }
          if (kb == nkb - 1 && type != T_QA) bar_arrive(3 + (wg ^ 1), 256);
          wg_fence();
#pragma unroll
          for (int ks = 0; ks < 4; ks++) {
            if (MD == 1) {
              wgmma_n128<1, 0>(acc[0], db + ks * 128, da + ks * 16, 1);
              wgmma_n128<1, 0>(acc[1], db + 1536 + ks * 128, da + ks * 16, 1);
            } else if (MD == 0) {
              wgmma_n128<0, 1>(acc[0], da + ks * 16, db + ks * 128, 1);
              wgmma_n128<0, 1>(acc[1], da + a_off + ks * 16, db + ks * 128, 1);
            } else {
              wgmma_n96<0, 1>(acc[0], da + ks * 16, db + ks * 64, 1);
              wgmma_n96<0, 1>(acc[1], da + 512 + ks * 16, db + ks * 64, 1);
            }
            if (ks == 0) wg_commit();
            if (ks == RELKS) {
              wg_wait<1>();
              arrive2_if(bar + B_EA + prev * 8, pd, l0 & (kb > 0), 1);
              mbar_arrive_if(bar + B_EB + eb * 8, l0 & (ec == PER) & last);
              if (ec == PER) { ec = 0; eb++; }
              ec++;
              wg_fence();
            }
            if (ks == TSTKS) {
              oka = mbar_test(bar + B_FA + nst * 8, nph);
              wg_fence();
            }
          }
          wg_commit();
          prev = st; st = nst; ph = nph;
        }
        wg_wait<0>();
      };
      if (type == T_V) mainloop(IntC<1>()); else if (type == T_OP || type == T_F2) mainloop(IntC<2>()); else mainloop(IntC<0>());
      arrive2_if(bar + B_EA + prev * 8, pd, l0, 1);
      mbar_arrive_if(bar + B_EB + 16, l0 & last);
      fence_regs(acc[0]); fence_regs(acc[1]);
      TR_T(tr1);
      unsigned* cnt;
      if (type <= T_V) {
        uint4* base = type == T_V ? g_Vf + (((size_t)sl * NSEG + rb * 4) * 8 + w) * 64 + lane : g_Kf + ((size_t)sl * 128 + rb * 8 + w) * 256 + lane;
        const int smb = type == T_V ? 256 : 1024, sq2 = type == T_V ? 512 : 64;
        const uint64_t pf = pol_first(); (void)pf;
#pragma unroll
        for (int mb = 0; mb < 2; mb++) {
#pragma unroll
          for (int q = 0; q < 8; q++) {
            const float* c = &acc[mb][q * 8];
            stg128_h(base + mb * smb + (q >> 1) * sq2 + (q & 1) * 32, pack2(c[0], c[1]), pack2(c[2], c[3]), pack2(c[4], c[5]), pack2(c[6], c[7]), pf);
          }
        }
        cnt = &g_kvflag[rb * 64 + type * 32 + sl];
      } else if (type == T_OP || type == T_F2) {
        uint4* base = (type == T_OP ? g_p1 : g_p2) + (((size_t)(rb * 16 + w * 2) * 18 + sl * 3) * SPL + kc) * 32 + lane;
#pragma unroll
        for (int u = 0; u < 3; u++)
#pragma unroll
          for (int mb = 0; mb < 2; mb++)
#pragma unroll
            for (int hi = 0; hi < 2; hi++) {
              const float* c = &acc[mb][u * 16 + hi * 2];
              stg128(base + ((mb * 8 + hi) * 18 + u) * (SPL * 32), pack2(c[0], c[1]), pack2(c[4], c[5]), pack2(c[8], c[9]), pack2(c[12], c[13]));
            }
        cnt = type == T_OP ? &g_cntP1[(rb) * PAD] : &g_cntP2[(rb) * PAD];
      } else if (type == T_F1) {
        uint4* base = g_gT + ((size_t)rb * 72 + sl * 2) * 1024 + w * 128 + j * 8 + g;
#pragma unroll
        for (int u = 0; u < 4; u++) {
          if (F1SPLIT && (d.y >> 28) == u + 1) break;
#pragma unroll
          for (int mb = 0; mb < 2; mb++) {
#pragma unroll
            for (int hi = 0; hi < 2; hi++) {
              uint32_t p[4];
#pragma unroll
              for (int i = 0; i < 4; i++) {
                const float* c = &acc[mb][(u * 4 + i) * 4 + hi * 2];
                p[i] = pack2(gelu_tanh(c[0]), gelu_tanh(c[1]));
              }
              stg128(base + (u >> 1) * 1024 + (mb * 8 + hi) * 64 + (u & 1) * 32, p[0], p[1], p[2], p[3]);
            }
          }
        }
        cnt = &g_cntG[(rb * 8 + sl / 6) * PAD];
      } else {
        uint32_t qa[2][8][4];
#pragma unroll
        for (int mb = 0; mb < 2; mb++)
#pragma unroll
          for (int ks = 0; ks < 8; ks++)
#pragma unroll
            for (int i = 0; i < 4; i++) qa[mb][ks][i] = pack2(acc[mb][ks * 8 + 2 * i], acc[mb][ks * 8 + 2 * i + 1]);
        float sc[2][5][4];
#pragma unroll
        for (int mb = 0; mb < 2; mb++)
#pragma unroll
          for (int n = 0; n < 5; n++) { sc[mb][n][0] = sc[mb][n][1] = sc[mb][n][2] = sc[mb][n][3] = 0.f; }
        auto stg_i = [&](int e) { const int q = st + e; return q >= NS ? q - NS : q; };
        auto stg_p = [&](int e) { return st + e >= NS ? ph ^ 1 : ph; };
        const int ek = w >> 1;
        const int em = (d.y >> 19) & 1 ? 2 : 4, ev = (em == 2 ? 3 : 2) + ek;
        const uint32_t woff = sb + SM_A + (w & 1) * 8192 + lane * 16;
        {
          mbar_wait(bar + B_FA + stg_i(ek) * 8, stg_p(ek), t0);
          const uint32_t ka = woff + stg_i(ek) * 16384;
          uint4 kf[16];
#pragma unroll
          for (int i = 0; i < 16; i++) kf[i] = lds128(ka + i * 512);
#pragma unroll
          for (int ks = 0; ks < 8; ks++) {
#pragma unroll
            for (int mb = 0; mb < 2; mb++) {
              mma16816(sc[mb][0], qa[mb][ks], kf[ks].x, kf[ks].z);
              mma16816(sc[mb][1], qa[mb][ks], kf[ks].y, kf[ks].w);
              mma16816(sc[mb][2], qa[mb][ks], kf[8 + ks].x, kf[8 + ks].z);
              if (mb == 1) mma16816(sc[mb][3], qa[mb][ks], kf[8 + ks].y, kf[8 + ks].w);
            }
          }
          __syncwarp();
          arrive2_if(bar + B_EA + stg_i(ek) * 8, pd, l0, 2);
        }
        uint4 vf[16], km[4], vm[4];
        {
          const uint32_t ma = sb + SM_A + stg_i(2) * 16384 + w * 2048 + lane * 16;
          mbar_wait(bar + B_FA + stg_i(em) * 8, stg_p(em), t0);
          if (em == 2) {
#pragma unroll
            for (int i = 0; i < 4; i++) km[i] = lds128(ma + i * 512);
#pragma unroll
            for (int i = 0; i < 4; i++) vm[i] = lds128(ma + 8192 + i * 512);
          } else {
            const unsigned need = epoch * 64 + rb * 4 + 4;
            while (true) {
              const int dd = (int)(ld_acquire(&g_memflag[sl * 8]) - need);
              if (__all_sync(~0u, dd >= 0 || timed_out(t0))) break;
              __nanosleep(rb >= URGENT ? 30 : 300);
            }
            const size_t mo = ((size_t)sl * NSEG + rb * 4 + w) * 128 + lane;
#pragma unroll
            for (int i = 0; i < 4; i++) km[i] = ldg_cg(g_Kmf + mo + i * 32);
#pragma unroll
            for (int i = 0; i < 4; i++) vm[i] = ldg_cg(g_Vmf + mo + i * 32);
          }
          float s2[2][4] = {{0.f, 0.f, 0.f, 0.f}, {0.f, 0.f, 0.f, 0.f}};
#pragma unroll
          for (int u = 0; u < 4; u++) {
#pragma unroll
            for (int mb = 0; mb < 2; mb++) {
              mma16816(sc[mb][4], qa[mb][2 * u], km[u].x, km[u].y);
              mma16816(s2[mb], qa[mb][2 * u + 1], km[u].z, km[u].w);
            }
          }
#pragma unroll
          for (int mb = 0; mb < 2; mb++)
#pragma unroll
            for (int i = 0; i < 4; i++) sc[mb][4][i] += s2[mb][i];
        }
        const bool early = EARLYHO && rb < URGENT;
        {
          mbar_wait(bar + B_FA + stg_i(ev) * 8, stg_p(ev), t0);
          if (early) bar_arrive(3 + (wg ^ 1), 256);
          const uint32_t va = woff + stg_i(ev) * 16384 + (__float_as_uint(sc[1][4][3]) & (d.y >> 30));
#pragma unroll
          for (int i = 0; i < 16; i++) vf[i] = lds128(va + i * 512);
          asm volatile("" :: "r"(vm[3].w), "r"(vf[15].w) : "memory");
          __syncwarp();
          arrive2_if(bar + B_EA + stg_i(ev) * 8, pd, l0, 2);
          arrive2_if(bar + B_EA + stg_i(em) * 8, pd, l0, 1);
        }
        const float scl = 0.08838834764831845f * 1.4426950408889634f;
        const float NEG = -INFINITY;
        uint32_t pa[2][5][2];
        float inv[2][2];
#pragma unroll
        for (int mb = 0; mb < 2; mb++) {
#pragma unroll
          for (int hi = 0; hi < 2; hi++) {
            const int nd = mb + 2 * hi;
            if (2 * j > g) sc[mb][nd][hi * 2] = NEG;
            if (2 * j + 1 > g) sc[mb][nd][hi * 2 + 1] = NEG;
            float m = fmaxf(sc[mb][4][hi * 2], sc[mb][4][hi * 2 + 1]);
#pragma unroll
            for (int n = 0; n < 4; n++) if (n <= nd) m = fmaxf(m, fmaxf(sc[mb][n][hi * 2], sc[mb][n][hi * 2 + 1]));
            m = fmaxf(m, __shfl_xor_sync(~0u, m, 1)); m = fmaxf(m, __shfl_xor_sync(~0u, m, 2));
            const float mc = m * scl;
            float l = 0.f;
#pragma unroll
            for (int n = 0; n < 5; n++) {
              if (n <= nd || n == 4) {
                const float e0 = ex2(fmaf(sc[mb][n][hi * 2], scl, -mc)), e1 = ex2(fmaf(sc[mb][n][hi * 2 + 1], scl, -mc));
                l += e0 + e1;
                pa[mb][n][hi] = pack2(e0, e1);
              } else pa[mb][n][hi] = 0u;
            }
            l += __shfl_xor_sync(~0u, l, 1); l += __shfl_xor_sync(~0u, l, 2);
            inv[mb][hi] = __fdividef(1.f, l);
          }
        }
        if ((__float_as_uint(inv[1][1]) & (d.y >> 30)) != 0) break;
        uint32_t op[4][2][2][4];
        uint4* obase = g_oT + ((size_t)rb * 64 + sl * 2) * 1024 + w * 256 + j * 8 + g;
#pragma unroll
        for (int u = 0; u < 4; u++) {
          float o[2][4][4];
#pragma unroll
          for (int mb = 0; mb < 2; mb++) {
#pragma unroll
            for (int i = 0; i < 4; i++) {
              o[mb][i][0] = o[mb][i][1] = o[mb][i][2] = o[mb][i][3] = 0.f;
              const uint4 v0 = vf[(2 * u + (i >> 1)) * 2], v1 = vf[(2 * u + (i >> 1)) * 2 + 1];
              const uint32_t vmw = i == 0 ? vm[u].x : i == 1 ? vm[u].y : i == 2 ? vm[u].z : vm[u].w;
              mma16816(o[mb][i], pa[mb][0][0], pa[mb][0][1], pa[mb][1][0], pa[mb][1][1], (i & 1) ? v0.y : v0.x, (i & 1) ? v0.w : v0.z);
              if (mb == 0) {
                mma16816(o[mb][i], pa[mb][2][0], pa[mb][2][1], pa[mb][4][0], pa[mb][4][1], (i & 1) ? v1.y : v1.x, vmw);
              } else {
                mma16816(o[mb][i], pa[mb][2][0], pa[mb][2][1], pa[mb][3][0], pa[mb][3][1], (i & 1) ? v1.y : v1.x, (i & 1) ? v1.w : v1.z);
                mma1688(o[mb][i], pa[mb][4][0], pa[mb][4][1], vmw);
              }
            }
          }
          if (u == 3 && !early) bar_arrive(3 + (wg ^ 1), 256);
#pragma unroll
          for (int mb = 0; mb < 2; mb++) {
#pragma unroll
            for (int hi = 0; hi < 2; hi++) {
              const float s = inv[mb][hi];
#pragma unroll
              for (int i = 0; i < 4; i++) op[u][mb][hi][i] = pack2(o[mb][i][hi * 2] * s, o[mb][i][hi * 2 + 1] * s);
            }
          }
        }
#pragma unroll
        for (int u = 0; u < 4; u++)
#pragma unroll
          for (int mb = 0; mb < 2; mb++)
#pragma unroll
            for (int hi = 0; hi < 2; hi++)
              stg128(obase + (u >> 1) * 1024 + (mb + 2 * hi) * 64 + (u & 1) * 32, op[u][mb][hi][0], op[u][mb][hi][1], op[u][mb][hi][2], op[u][mb][hi][3]);
        cnt = &g_cntO[(rb * 8 + (sl < 12 ? sl / 6 : 2 + (sl - 12) / 5)) * PAD];
      }
      if (rb >= URGENT && type >= T_QA) {
        bar_sync(1 + wg, 128);
        if (w == 0 && l0) red_release(cnt);
        cnt = nullptr;
      }
      mbar_wait(bar + B_PE + wg * 8, ((seq >> 1) & 1) ^ 1, t0);
      if (w == 0 && l0) {
        sts64(sb + SM_PUB + wg * 8, (uint32_t)(uintptr_t)cnt, (uint32_t)((uintptr_t)cnt >> 32));
        TR_LOG(d.x, tr0, tr1);
      }
      __syncwarp();
      mbar_arrive_if(bar + B_PD + wg * 8, l0);
    }
    __syncwarp();
    asm volatile("barrier.cluster.arrive.relaxed.aligned; barrier.cluster.wait.aligned;" ::: "memory");
  }
}
}
typedef CUresult (*EncodeFn)(CUtensorMap*, CUtensorMapDataType, cuuint32_t, void*, const cuuint64_t*, const cuuint64_t*, const cuuint32_t*,
                             const cuuint32_t*, CUtensorMapInterleave, CUtensorMapSwizzle, CUtensorMapL2promotion, CUtensorMapFloatOOBfill);
static EncodeFn get_encode() {
  void* fn = nullptr; cudaDriverEntryPointQueryResult st;
  cudaGetDriverEntryPoint("cuTensorMapEncodeTiled", &fn, cudaEnableDefault, &st);
  return (EncodeFn)fn;
}
static CUtensorMap map2d(EncodeFn enc, const void* p, int rows, int cols, int brow) {
  CUtensorMap m;
  cuuint64_t dim[2] = {(cuuint64_t)cols, (cuuint64_t)rows}; cuuint64_t str[1] = {(cuuint64_t)cols * 2};
  cuuint32_t box[2] = {64, (cuuint32_t)brow}, es[2] = {1, 1};
  enc(&m, CU_TENSOR_MAP_DATA_TYPE_BFLOAT16, 2, (void*)p, dim, str, box, es, CU_TENSOR_MAP_INTERLEAVE_NONE, CU_TENSOR_MAP_SWIZZLE_128B,
      CU_TENSOR_MAP_L2_PROMOTION_L2_256B, CU_TENSOR_MAP_FLOAT_OOB_FILL_NONE);
  return m;
}
static CUtensorMap map5d(EncodeFn enc, const void* p, int rows, int cols, int bcols) {
  CUtensorMap m;
  const cuuint64_t rs = (cuuint64_t)cols * 2;
  cuuint64_t dim[5] = {(cuuint64_t)cols, 2, 4, 4, (cuuint64_t)rows / 32}; cuuint64_t str[4] = {rs, 8 * rs, 2 * rs, 32 * rs};
  cuuint32_t box[5] = {(cuuint32_t)bcols, 2, 4, 4, bcols == 64 ? 6u : 8u}, es[5] = {1, 1, 1, 1, 1};
  enc(&m, CU_TENSOR_MAP_DATA_TYPE_BFLOAT16, 5, (void*)p, dim, str, box, es, CU_TENSOR_MAP_INTERLEAVE_NONE,
      bcols == 64 ? CU_TENSOR_MAP_SWIZZLE_128B : CU_TENSOR_MAP_SWIZZLE_64B,
      CU_TENSOR_MAP_L2_PROMOTION_L2_256B, CU_TENSOR_MAP_FLOAT_OOB_FILL_NONE);
  return m;
}
static CUtensorMap map3d(EncodeFn enc, const void* p, int brows) {
  CUtensorMap m;
  cuuint64_t dim[3] = {64, (cuuint64_t)DM, HD / 64}; cuuint64_t str[2] = {(cuuint64_t)HD * 2, 128};
  cuuint32_t box[3] = {64, (cuuint32_t)brows, 2}, es[3] = {1, 1, 1};
  enc(&m, CU_TENSOR_MAP_DATA_TYPE_BFLOAT16, 3, (void*)p, dim, str, box, es, CU_TENSOR_MAP_INTERLEAVE_NONE, CU_TENSOR_MAP_SWIZZLE_128B,
      CU_TENSOR_MAP_L2_PROMOTION_L2_256B, CU_TENSOR_MAP_FLOAT_OOB_FILL_NONE);
  return m;
}
template <typename... KArgs, typename... Args>
static void launch(void (*k)(KArgs...), int grid, int block, int smem, cudaStream_t s, int cluster, bool pdl, Args... args) {
  cudaLaunchConfig_t cfg = {};
  cfg.gridDim = dim3(grid); cfg.blockDim = dim3(block); cfg.dynamicSmemBytes = smem; cfg.stream = s;
  cudaLaunchAttribute at[2]; int n = 0;
  if (cluster > 1) { at[n].id = cudaLaunchAttributeClusterDimension; at[n].val.clusterDim.x = cluster; at[n].val.clusterDim.y = 1; at[n].val.clusterDim.z = 1; n++; }
  if (pdl) { at[n].id = cudaLaunchAttributeProgrammaticStreamSerialization; at[n].val.programmaticStreamSerializationAllowed = 1; n++; }
  cfg.attrs = at; cfg.numAttrs = n;
  cudaLaunchKernelEx(&cfg, k, KArgs(args)...);
}
struct Ctx {
  mega::Maps maps;
  chain::Maps cmaps;
  mega::WPtr wp;
  cudaStream_t s2; cudaEvent_t evFork, evJoin;
  bool init;
};
static void setup(Ctx& c, void* const* d_in) {
  EncodeFn enc = get_encode();
  c.maps.m[mega::T_K] = map3d(enc, d_in[3], 192); c.maps.m[mega::T_V] = map3d(enc, d_in[4], 192);
  c.maps.m[mega::T_QA] = map3d(enc, d_in[2], 192);
  c.maps.m[mega::T_OP] = map5d(enc, d_in[5], HD, DM, 32); c.maps.m[mega::T_F1] = map5d(enc, d_in[8], DM, FF, 64); c.maps.m[mega::T_F2] = map5d(enc, d_in[10], FF, DM, 32);
  { const int src[6] = {3, 4, 2, 5, 8, 10}; for (int i = 0; i < 6; i++) c.wp.p[i] = (const char*)d_in[src[i]]; }
  c.cmaps.q = map3d(enc, d_in[2], 16); c.cmaps.k = map3d(enc, d_in[3], 16); c.cmaps.v = map3d(enc, d_in[4], 16); c.cmaps.o = map2d(enc, d_in[5], HD, DM, 128);
  cudaFuncSetAttribute(chain::chain_kernel, cudaFuncAttributeNonPortableClusterSizeAllowed, 1);
  cudaFuncSetAttribute(chain::chain_kernel, cudaFuncAttributeMaxDynamicSharedMemorySize, chain::SM_TOTAL);
  cudaFuncSetAttribute(mega::mega_kernel, cudaFuncAttributeMaxDynamicSharedMemorySize, mega::SM_TOTAL);
  cudaFuncAttributes fa;
  cudaFuncGetAttributes(&fa, gate_kernel);
  int lo, hi; cudaDeviceGetStreamPriorityRange(&lo, &hi);
  cudaStreamCreateWithPriority(&c.s2, cudaStreamNonBlocking, hi);
  cudaEventCreateWithFlags(&c.evFork, cudaEventDisableTiming); cudaEventCreateWithFlags(&c.evJoin, cudaEventDisableTiming);
  c.init = true;
}
static Ctx g_ctx;
extern "C" void kernel_launch(void* const* d_in, const int* in_sizes, int n_in, void* d_out, int out_size) {
  Ctx& c = g_ctx;
  if (!c.init) setup(c, d_in);
  const bf16 *x = (const bf16*)d_in[0], *mem0 = (const bf16*)d_in[1], *b1 = (const bf16*)d_in[9], *b2 = (const bf16*)d_in[11];
  bf16* out = (bf16*)d_out;
  cudaStream_t s = cudaStreamPerThread;
  cudaEventRecord(c.evFork, s);
  cudaStreamWaitEvent(c.s2, c.evFork, 0);
  launch(chain::chain_kernel, 64, chain::NTHREADS, chain::SM_TOTAL, c.s2, 16, false, c.cmaps, mem0, x, (const bf16*)d_in[2], (const bf16*)d_in[3], (const bf16*)d_in[4], (const bf16*)d_in[5], b2, out, 0u);
  cudaEventRecord(c.evJoin, c.s2);
  launch(gate_kernel, 1, 1, 0, s, 1, false);
  launch(mega::mega_kernel, TAILW < NRB ? 124 : 132, 384, mega::SM_TOTAL, s, 2, true, c.maps, x, b1, b2, out, c.wp);
  cudaStreamWaitEvent(s, c.evJoin, 0);
}
```
